```python
import torch

def _softmax(x, axis=-1):
    return torch.softmax(x, dim=axis)
def _gelu(x):
    return torch.nn.functional.gelu(x, approximate="tanh")
def _silu(x):
    return torch.nn.functional.silu(x)
def _sigmoid(x):
    return torch.sigmoid(x)
def _layernorm(x, axis=-1, eps=1e-5):
    m = x.mean(dim=axis, keepdim=True)
    v = x.var(dim=axis, keepdim=True, unbiased=False)
    return (x - m) / torch.sqrt(v + eps)
def _scatter_add(tgt, idx, src, axis=0):
    return tgt.clone().index_add_(axis, idx, src)
def _segment_sum(src, seg, n):
    out = torch.zeros((n,) + src.shape[1:], dtype=src.dtype)
    return out.index_add_(0, seg, src)
def _pad(x, pw):
    flat = tuple(v for pair in reversed(pw) for v in pair)
    return torch.nn.functional.pad(x, flat)

kernel_name = 'sequential_preLN__linear_attn_block__glu_gated_bilinear__prompt'

def setup_inputs():

    _w = (lambda a: (lambda t: t.to(torch.bfloat16) if t.is_floating_point() else t)(torch.as_tensor(a)))
    def _A_setup():
        B, S, D = 1, 2048, 512
        return {
            "x": _w((lambda *s: torch.randn(*s, dtype=torch.bfloat16) * 0.05)(B, S, D)),
            "wqkv": _w((lambda *s: torch.randn(*s, dtype=torch.bfloat16) * 0.05)(D, 3 * D)),
            "wo": _w((lambda *s: torch.randn(*s, dtype=torch.bfloat16) * 0.05)(D, D)),
        }
    _A_in = _A_setup()

    def _B_setup():
        B, S, D, F = 1, 2048, 512, 1376
        return {
            "x": _w((lambda *s: torch.randn(*s, dtype=torch.bfloat16) * 0.05)(B, S, D)),
            "w_gate": _w((lambda *s: torch.randn(*s, dtype=torch.bfloat16) * 0.2)(D, F) * (D ** -0.5)),
            "w_up": _w((lambda *s: torch.randn(*s, dtype=torch.bfloat16) * 0.2)(D, F) * (D ** -0.5)),
            "w_down": _w((lambda *s: torch.randn(*s, dtype=torch.bfloat16) * 0.2)(F, D) * (F ** -0.5)),
        }
    _B_in = _B_setup()

    return {
        "A_x": _A_in["x"],
        "A_wqkv": _A_in["wqkv"],
        "A_wo": _A_in["wo"],
        "B_x": _B_in["x"],
        "B_w_gate": _B_in["w_gate"],
        "B_w_up": _B_in["w_up"],
        "B_w_down": _B_in["w_down"],
    }

def reference(A_x, A_wqkv, A_wo, B_x, B_w_gate, B_w_up, B_w_down):
    def _A_ref(x, wqkv, wo):
        B, S, D = x.shape
        H = 32; Dh = D // H
        qkv = (lambda x, *d: x.permute(*d))((x @ wqkv).reshape(B, S, 3, H, Dh), 2, 0, 3, 1, 4)
        q, k, v = qkv[0], qkv[1], qkv[2]
        phi = lambda t: torch.where(t > 0, t + 1, torch.exp(t)) + 1e-6
        pq, pk = phi(q), phi(k)
        kv = torch.einsum("bhsd,bhse->bhde", pk, v)
        z = torch.einsum("bhsd->bhd", pk)
        num = torch.einsum("bhqd,bhde->bhqe", pq, kv)
        den = torch.einsum("bhqd,bhd->bhq", pq, z)[..., None] + 1e-6
        o = num / den
        return (lambda x, *d: x.permute(*d))(o, 0, 2, 1, 3).reshape(B, S, D) @ wo

    def _B_ref(x, w_gate, w_up, w_down):
        g = torch.einsum("bsd,df->bsf", x, w_gate)
        u = torch.einsum("bsd,df->bsf", x, w_up)
        h = g * u
        return torch.einsum("bsf,fd->bsd", h, w_down)

    x = A_x
    h = x + _A_ref(_layernorm(x, axis=-1), A_wqkv, A_wo)
    h2 = h + _B_ref(_layernorm(h, axis=-1), B_w_gate, B_w_up, B_w_down)
    return h2
```

```cpp
#include <cuda_runtime.h>
#include <cuda_bf16.h>
#include <cuda.h>
#include <stdint.h>

namespace {

constexpr int S_TOK = 2048, DM = 512, FF = 1376;
constexpr int CL = 8, NCL = 15;
constexpr int TH = 69;
constexpr int TOKC = 2 * TH;
constexpr int SLOT_BYTES = 144 * 128;
constexpr int HALF_BYTES = 72 * 128;
constexpr int BOX_BYTES = TH * 128;
constexpr int TILE_TX = 2 * BOX_BYTES;
constexpr int WST = 5;
constexpr int WST_BYTES = 128 * 128;
constexpr int NFT = 22;

constexpr int OFF_ACT = 0;
constexpr int OFF_RING = 8 * SLOT_BYTES;
constexpr int OFF_STAT = OFF_RING + WST * WST_BYTES;
constexpr int OFF_BAR = OFF_STAT + 144 * 8;
constexpr int BAR_WFULL = OFF_BAR;
constexpr int BAR_WEMPTY = BAR_WFULL + WST * 8;
constexpr int BAR_AFULL = BAR_WEMPTY + WST * 8;
constexpr int BAR_AEMPTY = BAR_AFULL + 64;
constexpr int BAR_STAT = BAR_AEMPTY + 8;
constexpr int BAR_KVDONE = BAR_STAT + 8;
constexpr int BAR_KVRDY = BAR_KVDONE + 8;
constexpr int BAR_PUB = BAR_KVRDY + 8;
constexpr int BAR_VIS = BAR_PUB + 6 * 8;
constexpr int NBAR = 2 * WST + 8 + 4 + 6 + 5;
constexpr int OFF_EPOCH = BAR_VIS + 5 * 8;
constexpr int OFF_DUMMY = (OFF_EPOCH + 4 + 15) & ~15;
constexpr int SMEM_ALLOC = OFF_DUMMY + 16;
static_assert(SMEM_ALLOC <= 232448, "shared memory budget");

struct alignas(64) Params {
  CUtensorMap x, wqkv, wo, wg, wu, wd, scr, out;
  const __nv_bfloat16 *p_x, *p_wqkv, *p_wo, *p_wg, *p_wu, *p_wd;
  __nv_bfloat16* p_scr;
};

constexpr int SCR_TILES = 16 + NFT;
__device__ __align__(1024) __nv_bfloat16 g_scr[NCL * SCR_TILES * TOKC * 64];
__device__ __align__(128) float g_kv[2][32 * 272];
__device__ __align__(128) unsigned g_flag[8 * 32];
__device__ unsigned g_epoch;
#define TS(i)
#define TSW(i)
#define TS2(k, i)

__device__ __forceinline__ uint32_t smem_u32(const void* p) { return (uint32_t)__cvta_generic_to_shared(p); }
__device__ __forceinline__ void mbar_init(uint32_t bar, uint32_t cnt) {
  asm volatile("mbarrier.init.shared::cta.b64 [%0], %1;" ::"r"(bar), "r"(cnt) : "memory");
}
__device__ __forceinline__ void mbar_expect_tx(uint32_t bar, uint32_t bytes) {
  asm volatile("mbarrier.arrive.expect_tx.shared::cta.b64 _, [%0], %1;" ::"r"(bar), "r"(bytes) : "memory");
}
__device__ __forceinline__ void mbar_arrive(uint32_t bar) {
  asm volatile("mbarrier.arrive.shared::cta.b64 _, [%0];" ::"r"(bar) : "memory");
}
__device__ __forceinline__ void mbar_arrive_n(uint32_t bar, uint32_t n) {
  asm volatile("mbarrier.arrive.shared::cta.b64 _, [%0], %1;" ::"r"(bar), "r"(n) : "memory");
}
__device__ __forceinline__ uint32_t mapa(uint32_t addr, uint32_t cta) {
  uint32_t r;
  asm volatile("mapa.shared::cluster.u32 %0, %1, %2;" : "=r"(r) : "r"(addr), "r"(cta));
  return r;
}
__device__ __forceinline__ void mbar_arrive_remote(uint32_t bar, uint32_t cta) {
  asm volatile("mbarrier.arrive.shared::cluster.b64 _, [%0];" ::"r"(mapa(bar, cta)) : "memory");
}
__device__ __forceinline__ void mbar_arrive_remote_release(uint32_t bar, uint32_t cta) {
  asm volatile("mbarrier.arrive.release.cluster.shared::cluster.b64 _, [%0];" ::"r"(mapa(bar, cta)) : "memory");
}
constexpr int SPIN_LIMIT = 1 << 18;
__device__ __forceinline__ void mbar_wait(uint32_t bar, uint32_t parity) {
  uint32_t done;
  int it = 0;
  do {
    asm volatile(
        "{ .reg .pred p; mbarrier.try_wait.parity.shared::cta.b64 p, [%1], %2; selp.u32 %0, 1, 0, p; }"
        : "=r"(done) : "r"(bar), "r"(parity) : "memory");
  } while (!done && ++it < SPIN_LIMIT);
}
__device__ __forceinline__ void mbar_wait2(uint32_t bar0, uint32_t par0, uint32_t bar1, uint32_t par1) {
  uint32_t done;
  int it = 0;
  do {
    asm volatile(
        "{ .reg .pred p, q;\n"
        "mbarrier.try_wait.parity.shared::cta.b64 p, [%1], %2;\n"
        "mbarrier.try_wait.parity.shared::cta.b64 q, [%3], %4;\n"
        "and.pred p, p, q;\n"
        "selp.u32 %0, 1, 0, p; }"
        : "=r"(done) : "r"(bar0), "r"(par0), "r"(bar1), "r"(par1) : "memory");
  } while (!done && ++it < SPIN_LIMIT);
}
__device__ __forceinline__ uint32_t mbar_peek3(uint32_t w0, uint32_t pw0, uint32_t a0, uint32_t a1, uint32_t pa) {
  uint32_t done;
  asm volatile(
      "{ .reg .pred p, r, s;\n"
      "mbarrier.test_wait.parity.shared::cta.b64 p, [%1], %2;\n"
      "mbarrier.test_wait.parity.shared::cta.b64 r, [%3], %5;\n"
      "mbarrier.test_wait.parity.shared::cta.b64 s, [%4], %5;\n"
      "and.pred r, r, s;\n"
      "and.pred p, p, r;\n"
      "selp.u32 %0, 1, 0, p; }"
      : "=r"(done) : "r"(w0), "r"(pw0), "r"(a0), "r"(a1), "r"(pa) : "memory");
  return done;
}
__device__ __forceinline__ void mbar_arrive_pred(uint32_t bar, uint32_t cnt, bool pred) {
  asm volatile("{ .reg .pred p; setp.ne.b32 p, %2, 0; @p mbarrier.arrive.shared::cta.b64 _, [%0], %1; }" ::"r"(bar), "r"(cnt), "r"((int)pred) : "memory");
}
__device__ __forceinline__ void mbar_expect_tx_pred(uint32_t bar, uint32_t bytes, bool pred) {
  asm volatile("{ .reg .pred p; setp.ne.b32 p, %2, 0; @p mbarrier.arrive.expect_tx.shared::cta.b64 _, [%0], %1; }" ::"r"(bar), "r"(bytes), "r"((int)pred) : "memory");
}
__device__ __forceinline__ void mbar_arrive_remote_pred(uint32_t bar, uint32_t cta, bool pred) {
  asm volatile("{ .reg .pred p; .reg .b32 ra; setp.ne.b32 p, %2, 0; mapa.shared::cluster.u32 ra, %0, %1; @p mbarrier.arrive.shared::cluster.b64 _, [ra]; }" ::"r"(bar), "r"(cta), "r"((int)pred) : "memory");
}
__device__ __forceinline__ void st_async_v2(uint32_t raddr, float a, float b, uint32_t rbar) {
  asm volatile("st.async.weak.shared::cluster.mbarrier::complete_tx::bytes.v2.f32 [%0], {%1, %2}, [%3];" ::"r"(raddr), "f"(a), "f"(b),
               "r"(rbar) : "memory");
}
__device__ __forceinline__ uint2 ld_global_v2_pred(const void* p, bool pred) {
  uint2 v = make_uint2(0u, 0u);
  asm volatile("{ .reg .pred p; setp.ne.b32 p, %3, 0; @p ld.global.v2.b32 {%0, %1}, [%2]; }" : "+r"(v.x), "+r"(v.y) : "l"(p), "r"((int)pred) : "memory");
  return v;
}
__device__ __forceinline__ float2 ld_relaxed_v2(const float* p) {
  float2 v;
  asm volatile("ld.relaxed.gpu.global.v2.f32 {%0, %1}, [%2];" : "=f"(v.x), "=f"(v.y) : "l"(p) : "memory");
  return v;
}
__device__ __forceinline__ void st_global_v2_pred(void* p, uint32_t a, uint32_t b, bool pred) {
  asm volatile("{ .reg .pred p; setp.ne.b32 p, %3, 0; @p st.global.v2.b32 [%0], {%1, %2}; }" ::"l"(p), "r"(a), "r"(b), "r"((int)pred) : "memory");
}
__device__ __forceinline__ void mbar_wait_cluster(uint32_t bar, uint32_t parity) {
  uint32_t done;
  int it = 0;
  do {
    asm volatile(
        "{ .reg .pred p; mbarrier.try_wait.parity.acquire.cluster.shared::cta.b64 p, [%1], %2; selp.u32 %0, 1, 0, p; }"
        : "=r"(done) : "r"(bar), "r"(parity) : "memory");
  } while (!done && ++it < SPIN_LIMIT);
}
__device__ __forceinline__ void tma_load(uint32_t dst, const CUtensorMap* m, int c0, int c1, uint32_t bar) {
  asm volatile(
      "cp.async.bulk.tensor.2d.shared::cluster.global.mbarrier::complete_tx::bytes [%0], [%1, {%3, %4}], [%2];" ::"r"(dst),
      "l"(m), "r"(bar), "r"(c0), "r"(c1) : "memory");
}
__device__ __forceinline__ void tma_load_mc(uint32_t dst, const CUtensorMap* m, int c0, int c1, uint32_t bar) {
  asm volatile(
      "cp.async.bulk.tensor.2d.shared::cluster.global.mbarrier::complete_tx::bytes.multicast::cluster [%0], [%1, {%3, "
      "%4}], [%2], %5;" ::"r"(dst),
      "l"(m), "r"(bar), "r"(c0), "r"(c1), "h"((uint16_t)0xFF) : "memory");
}
__device__ __forceinline__ void tma_store(const CUtensorMap* m, int c0, int c1, uint32_t src) {
  asm volatile("cp.async.bulk.tensor.2d.global.shared::cta.bulk_group [%0, {%2, %3}], [%1];" ::"l"(m), "r"(src), "r"(c0),
               "r"(c1) : "memory");
}
__device__ __forceinline__ void bulk_commit() { asm volatile("cp.async.bulk.commit_group;" ::: "memory"); }
__device__ __forceinline__ void bulk_wait_all() { asm volatile("cp.async.bulk.wait_group 0;" ::: "memory"); }
__device__ __forceinline__ void bulk_wait_read() { asm volatile("cp.async.bulk.wait_group.read 0;" ::: "memory"); }
__device__ __forceinline__ void fence_async_smem() { asm volatile("fence.proxy.async.shared::cta;" ::: "memory"); }
__device__ __forceinline__ void prefetch_tmap(const CUtensorMap* m) {
  asm volatile("prefetch.tensormap [%0];" ::"l"(m) : "memory");
}
__device__ __forceinline__ void l2_prefetch(const void* p, uint32_t bytes) {
  asm volatile("cp.async.bulk.prefetch.L2.global [%0], %1;" ::"l"(p), "r"(bytes) : "memory");
}
#define WG_FENCE() asm volatile("wgmma.fence.sync.aligned;" ::: "memory")
#define WG_COMMIT() asm volatile("wgmma.commit_group.sync.aligned;" ::: "memory")
#define WG_WAIT(n) asm volatile("wgmma.wait_group.sync.aligned %0;" ::"n"(n) : "memory")
template <int N>
__device__ __forceinline__ void fence_acc(float (&d)[N]) {
#pragma unroll
  for (int i = 0; i < N; i++) asm volatile("" : "+f"(d[i])::"memory");
}
constexpr uint32_t DESC_HI = 0x40000000u | (1024 >> 4);
__device__ __forceinline__ uint32_t mk_desc(uint32_t addr) { return ((addr & 0x3FFFF) >> 4) | (1u << 16); }

__device__ __forceinline__ void wgmma_n72(float (&d)[36], uint32_t da, uint32_t db, int scale_d) {
  asm volatile("{ .reg .pred p; .reg .b64 da, db; setp.ne.b32 p, %38, 0;\n"
    "mov.b64 da, {%36, %39}; mov.b64 db, {%37, %39};\n"
    "wgmma.mma_async.sync.aligned.m64n72k16.f32.bf16.bf16 {"
    "%0,%1,%2,%3,%4,%5,%6,%7,%8,%9,%10,%11,"
    "%12,%13,%14,%15,%16,%17,%18,%19,%20,%21,%22,%23,"
    "%24,%25,%26,%27,%28,%29,%30,%31,%32,%33,%34,%35"
    "}, da, db, p, 1, 1, 1, 0; }"
    : "+f"(d[0]), "+f"(d[1]), "+f"(d[2]), "+f"(d[3]), "+f"(d[4]), "+f"(d[5]), "+f"(d[6]), "+f"(d[7]),
      "+f"(d[8]), "+f"(d[9]), "+f"(d[10]), "+f"(d[11]), "+f"(d[12]), "+f"(d[13]), "+f"(d[14]), "+f"(d[15]),
      "+f"(d[16]), "+f"(d[17]), "+f"(d[18]), "+f"(d[19]), "+f"(d[20]), "+f"(d[21]), "+f"(d[22]), "+f"(d[23]),
      "+f"(d[24]), "+f"(d[25]), "+f"(d[26]), "+f"(d[27]), "+f"(d[28]), "+f"(d[29]), "+f"(d[30]), "+f"(d[31]),
      "+f"(d[32]), "+f"(d[33]), "+f"(d[34]), "+f"(d[35])
    : "r"(da), "r"(db), "r"(scale_d), "r"(DESC_HI));
}

__device__ __forceinline__ void wgmma_n144(float (&d)[72], uint32_t da, uint32_t db, int scale_d) {
  asm volatile("{ .reg .pred p; .reg .b64 da, db; setp.ne.b32 p, %74, 0;\n"
    "mov.b64 da, {%72, %75}; mov.b64 db, {%73, %75};\n"
    "wgmma.mma_async.sync.aligned.m64n144k16.f32.bf16.bf16 {"
    "%0,%1,%2,%3,%4,%5,%6,%7,%8,%9,%10,%11,"
    "%12,%13,%14,%15,%16,%17,%18,%19,%20,%21,%22,%23,"
    "%24,%25,%26,%27,%28,%29,%30,%31,%32,%33,%34,%35,"
    "%36,%37,%38,%39,%40,%41,%42,%43,%44,%45,%46,%47,"
    "%48,%49,%50,%51,%52,%53,%54,%55,%56,%57,%58,%59,"
    "%60,%61,%62,%63,%64,%65,%66,%67,%68,%69,%70,%71"
    "}, da, db, p, 1, 1, 1, 0; }"
    : "+f"(d[0]), "+f"(d[1]), "+f"(d[2]), "+f"(d[3]), "+f"(d[4]), "+f"(d[5]), "+f"(d[6]), "+f"(d[7]),
      "+f"(d[8]), "+f"(d[9]), "+f"(d[10]), "+f"(d[11]), "+f"(d[12]), "+f"(d[13]), "+f"(d[14]), "+f"(d[15]),
      "+f"(d[16]), "+f"(d[17]), "+f"(d[18]), "+f"(d[19]), "+f"(d[20]), "+f"(d[21]), "+f"(d[22]), "+f"(d[23]),
      "+f"(d[24]), "+f"(d[25]), "+f"(d[26]), "+f"(d[27]), "+f"(d[28]), "+f"(d[29]), "+f"(d[30]), "+f"(d[31]),
      "+f"(d[32]), "+f"(d[33]), "+f"(d[34]), "+f"(d[35]), "+f"(d[36]), "+f"(d[37]), "+f"(d[38]), "+f"(d[39]),
      "+f"(d[40]), "+f"(d[41]), "+f"(d[42]), "+f"(d[43]), "+f"(d[44]), "+f"(d[45]), "+f"(d[46]), "+f"(d[47]),
      "+f"(d[48]), "+f"(d[49]), "+f"(d[50]), "+f"(d[51]), "+f"(d[52]), "+f"(d[53]), "+f"(d[54]), "+f"(d[55]),
      "+f"(d[56]), "+f"(d[57]), "+f"(d[58]), "+f"(d[59]), "+f"(d[60]), "+f"(d[61]), "+f"(d[62]), "+f"(d[63]),
      "+f"(d[64]), "+f"(d[65]), "+f"(d[66]), "+f"(d[67]), "+f"(d[68]), "+f"(d[69]), "+f"(d[70]), "+f"(d[71])
    : "r"(da), "r"(db), "r"(scale_d), "r"(DESC_HI));
}

__device__ __forceinline__ void mma16816(float (&c)[4], uint32_t a0, uint32_t a1, uint32_t a2, uint32_t a3, uint32_t b0,
                                         uint32_t b1) {
  asm volatile(
      "mma.sync.aligned.m16n8k16.row.col.f32.bf16.bf16.f32 {%0,%1,%2,%3}, {%4,%5,%6,%7}, {%8,%9}, {%0,%1,%2,%3};"
      : "+f"(c[0]), "+f"(c[1]), "+f"(c[2]), "+f"(c[3])
      : "r"(a0), "r"(a1), "r"(a2), "r"(a3), "r"(b0), "r"(b1));
}
__device__ __forceinline__ uint32_t movmat(uint32_t a) {
  uint32_t d;
  asm volatile("movmatrix.sync.aligned.m8n8.trans.b16 %0, %1;" : "=r"(d) : "r"(a));
  return d;
}
__device__ __forceinline__ void stsm4t(uint32_t addr, uint32_t r0, uint32_t r1, uint32_t r2, uint32_t r3) {
  asm volatile("stmatrix.sync.aligned.m8n8.x4.trans.shared.b16 [%0], {%1,%2,%3,%4};" ::"r"(addr), "r"(r0), "r"(r1),
               "r"(r2), "r"(r3) : "memory");
}
__device__ __forceinline__ void stsm2t(uint32_t addr, uint32_t r0, uint32_t r1) {
  asm volatile("stmatrix.sync.aligned.m8n8.x2.trans.shared.b16 [%0], {%1,%2};" ::"r"(addr), "r"(r0), "r"(r1) : "memory");
}
__device__ __forceinline__ void ldsm4t(uint32_t addr, uint32_t& r0, uint32_t& r1, uint32_t& r2, uint32_t& r3) {
  asm volatile("ldmatrix.sync.aligned.m8n8.x4.trans.shared.b16 {%0,%1,%2,%3}, [%4];"
               : "=r"(r0), "=r"(r1), "=r"(r2), "=r"(r3) : "r"(addr) : "memory");
}
__device__ __forceinline__ void ldsm2t(uint32_t addr, uint32_t& r0, uint32_t& r1) {
  asm volatile("ldmatrix.sync.aligned.m8n8.x2.trans.shared.b16 {%0,%1}, [%2];" : "=r"(r0), "=r"(r1) : "r"(addr) : "memory");
}
__device__ __forceinline__ float4 lds128f(uint32_t addr) {
  float4 v;
  asm volatile("ld.shared.v4.f32 {%0,%1,%2,%3}, [%4];" : "=f"(v.x), "=f"(v.y), "=f"(v.z), "=f"(v.w) : "r"(addr) : "memory");
  return v;
}
__device__ __forceinline__ float2 lds64f(uint32_t addr) {
  float2 v;
  asm volatile("ld.shared.v2.f32 {%0,%1}, [%2];" : "=f"(v.x), "=f"(v.y) : "r"(addr) : "memory");
  return v;
}
__device__ __forceinline__ uint4 lds128u(uint32_t addr) {
  uint4 v;
  asm volatile("ld.shared.v4.u32 {%0,%1,%2,%3}, [%4];" : "=r"(v.x), "=r"(v.y), "=r"(v.z), "=r"(v.w) : "r"(addr) : "memory");
  return v;
}
__device__ __forceinline__ uint32_t pack_bf16(float lo, float hi) {
  uint32_t r;
  asm("cvt.rn.bf16x2.f32 %0, %1, %2;" : "=r"(r) : "f"(hi), "f"(lo));
  return r;
}
__device__ __forceinline__ float bf_lo(uint32_t p) { return __uint_as_float(p << 16); }
__device__ __forceinline__ float bf_hi(uint32_t p) { return __uint_as_float(p & 0xFFFF0000u); }
__device__ __forceinline__ float ex2(float t) {
  float r;
  asm("ex2.approx.ftz.f32 %0, %1;" : "=f"(r) : "f"(t));
  return r;
}
__device__ __forceinline__ uint32_t hadd2(uint32_t a, uint32_t b) {
  uint32_t r;
  asm("add.rn.bf16x2 %0, %1, %2;" : "=r"(r) : "r"(a), "r"(b));
  return r;
}
__device__ __forceinline__ uint32_t hmul2(uint32_t a, uint32_t b) {
  uint32_t r;
  asm("mul.rn.bf16x2 %0, %1, %2;" : "=r"(r) : "r"(a), "r"(b));
  return r;
}
__device__ __forceinline__ void red_add_v2(float* p, float a, float b) {
  asm volatile("red.relaxed.gpu.global.add.v2.f32 [%0], {%1, %2};" ::"l"(p), "f"(a), "f"(b) : "memory");
}

template <int N>
__device__ __forceinline__ void wgmma(float (&d)[N / 2], uint32_t da, uint32_t db, int scale_d) {
  if constexpr (N == 144) wgmma_n144(d, da, db, scale_d);
  else wgmma_n72(d, da, db, scale_d);
}

struct Ring {
  int ws, ph;
  __device__ __forceinline__ void advance() { if (++ws == WST) { ws = 0; ph ^= 1; } }
};

template <int N, bool SAME>
__device__ __forceinline__ void mma_loop(float (&accA)[N / 2], float (&accB)[N / 2], Ring& R, uint32_t sb, uint32_t actB, int n,
                                         int par0, int parmask, uint32_t relcnt, int relsteps, bool arm, int t128, int sigbar,
                                         int dbg) {
  const uint32_t wlo = mk_desc(sb + OFF_RING), alo = mk_desc(actB);
  const bool lead = t128 == 0, lead2 = t128 < (SAME ? 2 : 1);
  const uint32_t l = SAME ? (t128 & 1) : 0;
  auto release = [&](int i, int stage) {
    mbar_arrive_pred(sb + BAR_WEMPTY + 8 * stage, relcnt, lead);
    const uint32_t sl = (SAME ? ((2 * i) & 7) : i) + l;
    const bool mine = (i < relsteps) && lead2;
    mbar_expect_tx_pred(sb + BAR_AFULL + 8 * sl, TILE_TX, mine && arm);
    mbar_arrive_remote_pred(sb + BAR_AEMPTY, sl, mine);
  };
  uint32_t tok = 0;
  int prev = 0;
#pragma unroll 1
  for (int i = 0; i < n; i++) {
    const int ws = R.ws;
    const int a = SAME ? ((2 * i) & 7) : i;
    if (!tok) {
      const int pa = (par0 + ((i >> 2) & parmask)) & 1;
      mbar_wait(sb + BAR_WFULL + 8 * ws, R.ph);
      mbar_wait2(sb + BAR_AFULL + 8 * a, pa, sb + BAR_AFULL + 8 * a + (SAME ? 8 : 0), pa);
    }
    if (t128 == 0) TS2(1 + (threadIdx.x >> 7), dbg + i);
    R.advance();
    const uint32_t da = wlo + ws * (WST_BYTES >> 4), db = alo + a * (SLOT_BYTES >> 4);
    WG_FENCE();
#pragma unroll
    for (int kk = 0; kk < 3; kk++) wgmma<N>(accA, da + kk * 128, db + kk * 2, 1);
    WG_COMMIT();
    const int i1 = i + 1, a1 = SAME ? ((2 * i1) & 7) : (i1 & 7);
    tok = mbar_peek3(sb + BAR_WFULL + 8 * R.ws, R.ph, sb + BAR_AFULL + 8 * a1, sb + BAR_AFULL + 8 * a1 + (SAME ? 8 : 0),
                     (par0 + ((i1 >> 2) & parmask)) & 1);
    if (sigbar && i == n - 1) asm volatile("bar.arrive %0, 256;" ::"r"(sigbar) : "memory");
    WG_WAIT(1);
    if (i > 0) release(i - 1, prev);
    prev = ws;
    wgmma<N>(accA, da + 384, db + 6, 1);
    if constexpr (SAME) {
#pragma unroll
      for (int kk = 0; kk < 4; kk++) wgmma<N>(accA, da + 512 + kk * 128, db + (SLOT_BYTES >> 4) + kk * 2, 1);
    } else {
#pragma unroll
      for (int kk = 0; kk < 4; kk++) wgmma<N>(accB, da + 512 + kk * 128, db + kk * 2, 1);
    }
    WG_COMMIT();
  }
  WG_WAIT(0);
  fence_acc(accA);
  if constexpr (!SAME) fence_acc(accB);
  release(n - 1, prev);
}

__device__ __forceinline__ void stage_frag(uint32_t a, uint32_t a8, const uint32_t (&p)[18]) {
#pragma unroll
  for (int jj = 0; jj < 8; jj += 2) stsm4t(a + jj * 1024, p[2 * jj], p[2 * jj + 1], p[2 * jj + 2], p[2 * jj + 3]);
  stsm2t(a8, p[16], p[17]);
  fence_async_smem();
  __syncwarp();
}
__device__ __forceinline__ void load_frag(uint32_t a, uint32_t (&p)[18]) {
#pragma unroll
  for (int jj = 0; jj < 8; jj += 2) ldsm4t(a + jj * 1024, p[2 * jj], p[2 * jj + 1], p[2 * jj + 2], p[2 * jj + 3]);
  ldsm2t(a + 8 * 1024, p[16], p[17]);
}
__device__ __forceinline__ void store_frag(char* d, const uint32_t (&p)[18], int q) {
#pragma unroll
  for (int jj = 0; jj < 9; jj++) {
    const uint32_t lo = movmat(p[2 * jj]), hi = movmat(p[2 * jj + 1]);
    const uint32_t recv = __shfl_xor_sync(0xffffffffu, (q & 1) ? lo : hi, 1);
    st_global_v2_pred(d + jj * 1024, (q & 1) ? recv : lo, (q & 1) ? hi : recv, jj < 8 || (threadIdx.x & 31) < 4 * (TH - 64));
  }
}

__global__ void __launch_bounds__(384, 1) fused_kernel(const __grid_constant__ Params P) {
  extern __shared__ __align__(1024) uint8_t smem_raw[];
  const uint32_t sb = smem_u32(smem_raw);
  const int tid = threadIdx.x, warp = __shfl_sync(0xffffffffu, tid >> 5, 0), lane = tid & 31;
  uint32_t rank;
  asm volatile("mov.u32 %0, %%cluster_ctarank;" : "=r"(rank));
  const int j = (int)rank;
  const int cl = blockIdx.x / CL;
  const int tok0 = cl * TOKC;
  const int nr = (j + 16 < NFT) ? 3 : 2;

  {
    const char* wp = reinterpret_cast<const char*>(P.p_wqkv) + (size_t)(tid >> 1) * (3 * DM * 2) + (512 + 512 * (tid & 1) + 64 * j) * 2;
    asm volatile("prefetch.global.L2 [%0];" ::"l"(wp) : "memory");
  }
  if (warp == 8) {
    for (int b = lane; b < NBAR; b += 32) {
      uint32_t cnt = 1;
      if (b >= WST && b < 2 * WST) cnt = 2;
      const int o = b - (2 * WST + 8);
      if (o == 0) cnt = 16;
      if (o == 2 || (o >= 4 && o < 10)) cnt = 8;
      mbar_init(sb + OFF_BAR + 8 * b, cnt);
    }
    asm volatile("fence.mbarrier_init.release.cluster;" ::: "memory");
    __syncwarp();
    if (lane < 9) mbar_expect_tx(lane < 8 ? sb + BAR_AFULL + 8 * lane : sb + BAR_STAT, lane < 8 ? TILE_TX : 144 * 8);
  } else if (warp == 9) {
    if (lane < 8) prefetch_tmap(&P.x + lane);
  }
  uint4 v[5][2];
  if (warp >= 4 && warp < 8) {
#pragma unroll
    for (int i = 0; i < 5; i++) {
      const int row = 18 * j + min((warp & 3) + 4 * i, 17);
      const int tk = min(tok0 + row - (row >= 72 ? 3 : 0), S_TOK - 1);
      const uint4* src = reinterpret_cast<const uint4*>(P.p_x + (size_t)tk * DM) + lane;
      v[i][0] = __ldg(src);
      v[i][1] = __ldg(src + 32);
    }
  }
  if (warp < 4 && lane < 24) {
#pragma unroll
    for (int k = 0; k < 4; k++)
      asm volatile("st.shared.v4.u32 [%0], {%1,%1,%1,%1};" ::"r"(sb + OFF_ACT + (warp + 4 * k) * HALF_BYTES + 69 * 128 + lane * 16),
                   "r"(lane >= 16 ? 0x3F803F80u : 0u) : "memory");
    fence_async_smem();
  }
  __syncthreads();
  if (warp == 8) asm volatile("barrier.cluster.arrive.release.aligned;" ::: "memory");
  else asm volatile("barrier.cluster.arrive.relaxed.aligned;" ::: "memory");

  if (warp >= 8) {
    if (lane == 0) {
      if (warp == 8) {
#pragma unroll 1
        for (int n = 0; n < 3; n++) {
          const uint32_t dst = sb + OFF_RING + n * WST_BYTES, bar = sb + BAR_WFULL + 8 * n;
          mbar_expect_tx(bar, WST_BYTES);
          tma_load(dst, &P.wqkv, 64 * j + 512, 64 * n, bar);
          tma_load(dst + WST_BYTES / 2, &P.wqkv, 64 * j + 1024, 64 * n, bar);
        }
      } else {
#pragma unroll 1
        for (int s = warp - 9; s < 8; s += 3) {
          tma_load(sb + OFF_ACT + s * SLOT_BYTES, &P.x, 64 * s, tok0, sb + BAR_AFULL + 8 * s);
          tma_load(sb + OFF_ACT + s * SLOT_BYTES + HALF_BYTES, &P.x, 64 * s, tok0 + TH, sb + BAR_AFULL + 8 * s);
        }
      }
    }
    __syncwarp();
    asm volatile("setmaxnreg.dec.sync.aligned.u32 40;");
    if (warp == 8) {
      if (lane == 0) {
        const int nstage = 16 + 8 * nr + NFT / 2;
        int st = 3, ph = 1;
#pragma unroll 1
        for (int n = 3; n < nstage; n++) {
          const uint32_t dst = sb + OFF_RING + st * WST_BYTES, bar = sb + BAR_WFULL + 8 * st;
          if (n >= WST) mbar_wait(sb + BAR_WEMPTY + 8 * st, ph);
          if (++st == WST) { st = 0; ph ^= 1; }
          TS2(0, n);
          mbar_expect_tx(bar, WST_BYTES);
          const CUtensorMap *m0, *m1;
          int c0 = 64 * j, c1 = c0, r0, r1;
          if (n < 8) { m0 = m1 = &P.wqkv; c0 += 512; c1 += 1024; r0 = r1 = 64 * n; }
          else if (n < 16) { m0 = m1 = n < 12 ? &P.wqkv : &P.wo; r0 = 128 * (n & 3); r1 = r0 + 64; }
          else if (n < 16 + 8 * nr) { m0 = &P.wg; m1 = &P.wu; c0 += 512 * ((n - 16) >> 3); c1 = c0; r0 = r1 = 64 * (n & 7); }
          else { m0 = m1 = &P.wd; r0 = 128 * (n - 16 - 8 * nr); r1 = r0 + 64; }
          tma_load(dst, m0, c0, r0, bar);
          tma_load(dst + WST_BYTES / 2, m1, c1, r1, bar);
        }
      }
    } else if (warp == 9) {
      asm volatile("barrier.cluster.wait.acquire.aligned;" ::: "memory");
      if (lane == 0) {
        const uint32_t slot = sb + OFF_ACT + j * SLOT_BYTES, af = sb + BAR_AFULL + 8 * j;
#pragma unroll 1
        for (int e = 1; e < 3 + nr; e++) {
          const int row = (cl * SCR_TILES + 8 * (e - 1) + j) * TOKC;
          mbar_wait(sb + BAR_VIS + 8 * (e - 1), 0);
          asm volatile("fence.proxy.async.global;" ::: "memory");
          TSW(2 * e - 1);
          mbar_wait(sb + BAR_AEMPTY, (e - 1) & 1);
          tma_load_mc(slot, &P.scr, 0, row, af);
          tma_load_mc(slot + HALF_BYTES, &P.scr, 0, row + TH, af);
          TSW(2 * e);
        }
      }
    } else if (warp == 10) {
      unsigned epoch = 0;
      if (lane == 0) asm volatile("ld.relaxed.gpu.global.u32 %0, [%1];" : "=r"(epoch) : "l"(&g_epoch) : "memory");
      epoch = __shfl_sync(0xffffffffu, epoch, 0);
      if (lane == 0) asm volatile("st.shared.u32 [%0], %1;" ::"r"(sb + OFF_EPOCH), "r"(epoch) : "memory");
      __syncwarp();
      asm volatile("bar.arrive 12, 160;" ::: "memory");
      asm volatile("bar.arrive 13, 160;" ::: "memory");
      if (cl == 0) {
        float* z = &g_kv[(epoch + 1) & 1][j * 4 * 272];
#pragma unroll 1
        for (int i = lane; i < 4 * 272; i += 32) z[i] = 0.f;
      }
      mbar_wait(sb + BAR_KVDONE, 0);
      TSW(20);
      const unsigned target = (epoch + 1u) * NCL;
      if (lane == 0) {
        asm volatile("fence.acq_rel.gpu;" ::: "memory");
        asm volatile("red.relaxed.gpu.global.add.u32 [%0], %1;" ::"l"(&g_flag[j * 32]), "r"(1u) : "memory");
        TSW(21);
        unsigned v;
        int n = 0;
        do {
          asm volatile("ld.acquire.gpu.global.u32 %0, [%1];" : "=r"(v) : "l"(&g_flag[j * 32]) : "memory");
        } while ((int)(v - target) < 0 && ++n < SPIN_LIMIT);
      }
      __syncwarp();
      TSW(22);
      if (lane == 0) mbar_arrive(sb + BAR_KVRDY);
      if (blockIdx.x == 0) {
        unsigned v2 = target;
        int n = 0;
        do {
          if (lane < 8) asm volatile("ld.acquire.gpu.global.u32 %0, [%1];" : "=r"(v2) : "l"(&g_flag[lane * 32]) : "memory");
        } while (__any_sync(0xffffffffu, (int)(v2 - target) < 0) && ++n < SPIN_LIMIT);
        if (lane == 0) asm volatile("st.relaxed.gpu.global.u32 [%0], %1;" ::"l"(&g_epoch), "r"(epoch + 1u) : "memory");
      }
    } else {
      mbar_wait(sb + BAR_AFULL + 8 * 7, 0);
      if (lane < 4) {
        const uint32_t total = lane == 0 ? 512u * 512u * 2u : 512u * 1376u * 2u;
        const uint32_t chunk = lane == 0 ? 4480u : 11776u;
        const char* base = (const char*)(lane == 0 ? P.p_wo : lane == 1 ? P.p_wg : lane == 2 ? P.p_wu : P.p_wd);
        const uint32_t off = blockIdx.x * chunk;
        if (off < total) l2_prefetch(base + off, min(chunk, total - off));
      }
      if (lane == 0) {
        const uint32_t slot = sb + OFF_ACT + j * SLOT_BYTES;
#pragma unroll 1
        for (int e = 0; e < 3 + nr; e++) {
          const bool last = (e == 2 + nr);
          mbar_wait(sb + BAR_PUB + 8 * (last ? 5 : e), 0);
          if (e < 2 || last) {
            const CUtensorMap* m = last ? &P.out : &P.scr;
            const int c0 = last ? 64 * j : 0, c1 = last ? tok0 : (cl * SCR_TILES + 8 * e + j) * TOKC;
            tma_store(m, c0, c1, slot);
            tma_store(m, c0, c1 + TH, slot + HALF_BYTES);
            bulk_commit();
            if (last) { bulk_wait_read(); break; }
            bulk_wait_all();
          } else {
            asm volatile("fence.acq_rel.gpu;" ::: "memory");
          }
          mbar_arrive(sb + BAR_VIS + 8 * e);
        }
      }
    }
  } else {
    asm volatile("setmaxnreg.inc.sync.aligned.u32 232;");
    const int w = warp >> 2, w4 = warp & 3;
    const uint32_t act0 = sb + OFF_ACT;
    const int tokw = tok0 + w * TH;
    Ring R = {0, 0};
    int nw = 0;
    uint32_t hres[18];

#pragma unroll 1
    for (int t = 0; t < 4; t++) {
      int lane = tid & 31;
      asm volatile("" : "+r"(lane));
      const int g = lane >> 2, q = lane & 3, t128 = w4 * 32 + lane;
      const int nvalid = min(TH, S_TOK - tokw);
      const uint32_t loff = (uint32_t)((8 * (lane >> 4) + (lane & 7)) * 128 + (((2 * w4 + ((lane >> 3) & 1)) ^ (lane & 7)) << 4));
      const bool tail_ok = (lane & 7) < TH - 64;
      if (w == 1 && (t == 0 || t == 3)) {
        if (t == 3) {
#pragma unroll 1
          for (int s = 0; s < 8; s++) mbar_wait(sb + BAR_AFULL + 8 * s, 0);
#pragma unroll
          for (int i = 0; i < 5; i++) {
            const int row = 18 * j + min(w4 + 4 * i, 17);
            const uint32_t a = act0 + (lane >> 3) * SLOT_BYTES + row * 128 + (((lane & 7) ^ (row & 7)) << 4);
            v[i][0] = lds128u(a);
            v[i][1] = lds128u(a + 4 * SLOT_BYTES);
          }
        }
        float s1[5], s2[5], piv[5];
#pragma unroll
        for (int i = 0; i < 5; i++) {
          piv[i] = __shfl_sync(0xffffffffu, bf_lo(v[i][0].x), 0);
          s1[i] = 0.f; s2[i] = 0.f;
#pragma unroll
          for (int k = 0; k < 2; k++) {
            const uint32_t u[4] = {v[i][k].x, v[i][k].y, v[i][k].z, v[i][k].w};
#pragma unroll
            for (int e = 0; e < 4; e++) {
              const float d0 = bf_lo(u[e]) - piv[i], d1 = bf_hi(u[e]) - piv[i];
              s1[i] += d0 + d1;
              s2[i] = fmaf(d0, d0, fmaf(d1, d1, s2[i]));
            }
          }
        }
#pragma unroll
        for (int o = 1; o < 32; o <<= 1) {
#pragma unroll
          for (int i = 0; i < 5; i++) {
            s1[i] += __shfl_xor_sync(0xffffffffu, s1[i], o);
            s2[i] += __shfl_xor_sync(0xffffffffu, s2[i], o);
          }
        }
        if (t == 0) asm volatile("barrier.cluster.wait.acquire.aligned;" ::: "memory");
        if (lane < CL) {
          const uint32_t rstat = mapa(sb + OFF_STAT, lane), rbar = mapa(sb + BAR_STAT, lane);
#pragma unroll
          for (int i = 0; i < 5; i++) {
            const int row = 18 * j + w4 + 4 * i;
            const int hf = row >= 72, rr = row - 72 * hf;
            const float md = s1[i] * (1.f / DM);
            const float var = fmaxf(s2[i] * (1.f / DM) - md * md, 0.f);
            const bool valid = rr < TH && tok0 + hf * TH + rr < S_TOK;
            if (w4 + 4 * i < 18) st_async_v2(rstat + row * 8, piv[i] + md, valid ? rsqrtf(var + 1e-5f) : 0.f, rbar);
          }
        }
        TS(10 + (t >> 1));
      } else if (t == 0) {
        asm volatile("barrier.cluster.wait.acquire.aligned;" ::: "memory");
      }
#pragma unroll
      for (int i = 0; i < 5; i++) v[i][0] = v[i][1] = make_uint4(0u, 0u, 0u, 0u);
      auto fetch_res = [&]() {
        mbar_wait(sb + BAR_AFULL + 8 * j, 0);
        load_frag(act0 + j * SLOT_BYTES + w * HALF_BYTES + loff, hres);
      };
      if (t == 3) {
#pragma unroll
        for (int i = 0; i < 18; i++) hres[i] = 0u;
#pragma unroll 1
        for (int r = 0; r < nr; r++) {
          const bool split = (r == 2);
          if (!split && r != w) {
            asm volatile("bar.sync %0, 256;" ::"r"(2 + r) : "memory");
#pragma unroll 1
            for (int i = 0; i < 8; i++) R.advance();
            nw += 8;
            continue;
          }
          float accA[72], accB[72];
          const bool lastread = split || nr == 2;
          if (lastread) fetch_res();
#pragma unroll
          for (int i = 0; i < 36; i++) { accA[i] = 0.f; accB[i] = 0.f; }
          if (split) {
            mma_loop<72, false>(reinterpret_cast<float(&)[36]>(accA), reinterpret_cast<float(&)[36]>(accB), R, sb,
                                act0 + w * HALF_BYTES, 8, 0, 0, 1, 8, w == 0, t128, 0, nw);
          } else {
#pragma unroll
            for (int i = 36; i < 72; i++) { accA[i] = 0.f; accB[i] = 0.f; }
            mma_loop<144, false>(accA, accB, R, sb, act0, 8, 0, 0, 2, lastread ? 8 : 0, w == 0, t128, 2 + r, nw);
          }
          nw += 8;
          TS(3 + 1 + r);
          mbar_wait(sb + BAR_STAT, 1);
#pragma unroll 1
          for (int hf = split ? w : 0; hf < (split ? w + 1 : 2); hf++) {
            const float a0 = __shfl_sync(0xffffffffu, accA[33], lane | 3), a1 = __shfl_sync(0xffffffffu, accA[35], lane | 3);
            const float b0 = __shfl_sync(0xffffffffu, accB[33], lane | 3), b1 = __shfl_sync(0xffffffffu, accB[35], lane | 3);
            uint32_t p[18];
            float4 sts[9];
#pragma unroll
            for (int jj = 0; jj < 9; jj++) sts[jj] = lds128f(sb + OFF_STAT + (72 * hf + 8 * jj + 2 * q) * 8);
#pragma unroll
            for (int jj = 0; jj < 9; jj++) {
              const float4 st = sts[jj];
              const float r0 = st.y * st.y, r1 = st.w * st.w;
              p[2 * jj] = pack_bf16(r0 * (fmaf(-st.x, a0, accA[4 * jj]) * fmaf(-st.x, b0, accB[4 * jj])),
                                    r1 * (fmaf(-st.z, a0, accA[4 * jj + 1]) * fmaf(-st.z, b0, accB[4 * jj + 1])));
              p[2 * jj + 1] = pack_bf16(r0 * (fmaf(-st.x, a1, accA[4 * jj + 2]) * fmaf(-st.x, b1, accB[4 * jj + 2])),
                                        r1 * (fmaf(-st.z, a1, accA[4 * jj + 3]) * fmaf(-st.z, b1, accB[4 * jj + 3])));
            }
            store_frag(reinterpret_cast<char*>(P.p_scr) + (size_t)((cl * SCR_TILES + 16 + 8 * r + j) * TOKC + hf * TH + g) * 128 +
                           (16 * w4 + (q & 1) * 8 + (q >> 1) * 4) * 2, p, q);
            if (!split) {
#pragma unroll
              for (int i = 0; i < 36; i++) { accA[i] = accA[i + 36]; accB[i] = accB[i + 36]; }
            }
          }
          __syncwarp();
          mbar_arrive_pred(sb + BAR_PUB + 8 * (2 + r), split ? 1 : 2, lane == 0);
          TS(16 + 4 + r);
        }
      }
      if (t == 1) fetch_res();
      float acc[36];
      uint32_t pv[18];
      if (t >= 2) {
#pragma unroll
        for (int i = 0; i < 18; i++) {
          acc[(i >> 1) * 4 + (i & 1) * 2] = bf_lo(hres[i]);
          acc[(i >> 1) * 4 + (i & 1) * 2 + 1] = bf_hi(hres[i]);
        }
      } else {
#pragma unroll
        for (int i = 0; i < 36; i++) acc[i] = 0.f;
      }
      auto load_stats = [&](float4 (&st)[9]) {
#pragma unroll
        for (int jj = 0; jj < 9; jj++) st[jj] = lds128f(sb + OFF_STAT + (72 * w + 8 * jj + 2 * q) * 8);
      };
      if (t == 0) {
        float av[36];
#pragma unroll
        for (int i = 0; i < 36; i++) av[i] = 0.f;
        mma_loop<72, false>(acc, av, R, sb, act0 + w * HALF_BYTES, 8, 0, 0, 1, 0, w == 0, t128, 0, nw);
        nw += 8;
        TS(1);
        mbar_wait(sb + BAR_STAT, 0);
        mbar_expect_tx_pred(sb + BAR_STAT, 144 * 8, tid == 0);
        const float c0 = __shfl_sync(0xffffffffu, av[33], lane | 3), c1 = __shfl_sync(0xffffffffu, av[35], lane | 3);
        float4 st[9];
        load_stats(st);
#pragma unroll
        for (int jj = 0; jj < 9; jj++) {
          pv[2 * jj] = pack_bf16(st[jj].y * fmaf(-st[jj].x, c0, av[4 * jj]), st[jj].w * fmaf(-st[jj].z, c0, av[4 * jj + 1]));
          pv[2 * jj + 1] = pack_bf16(st[jj].y * fmaf(-st[jj].x, c1, av[4 * jj + 2]), st[jj].w * fmaf(-st[jj].z, c1, av[4 * jj + 3]));
        }
      } else {
        mma_loop<72, true>(acc, acc, R, sb, act0 + w * HALF_BYTES, t == 3 ? NFT / 2 : 4, t == 1 ? 0 : t == 2 ? 1 : 3, t == 3 ? 3 : 0, 1,
                           t == 3 ? (NFT - 8) / 2 : 4, w == 0, t128, 0, nw);
        nw += 4;
        TS(t == 3 ? 7 : t + 1);
      }
      uint32_t p[18];
      if (t < 2) {
        const float c0 = __shfl_sync(0xffffffffu, acc[33], lane | 3), c1 = __shfl_sync(0xffffffffu, acc[35], lane | 3);
        float4 st[9];
        load_stats(st);
#pragma unroll
        for (int i = 0; i < 36; i++) {
          const float m = (i & 1) ? st[i >> 2].z : st[i >> 2].x;
          const float rr = (i & 1) ? st[i >> 2].w : st[i >> 2].y;
          const float u = fmaf(-m, (i & 2) ? c1 : c0, acc[i]);
          const float tl = rr * 1.4426950408889634f * u;
          acc[i] = fmaxf(fmaf(rr, u, 1e-6f), 1e-6f) + ex2(fminf(tl, 0.f));
        }
      }
#pragma unroll
      for (int i = 0; i < 18; i++) p[i] = pack_bf16(acc[(i >> 1) * 4 + (i & 1) * 2], acc[(i >> 1) * 4 + (i & 1) * 2 + 1]);
      if (t == 0) {
        float dkv[2][4] = {}, dz[2][4] = {};
#pragma unroll
        for (int s = 0; s < 5; s++) {
          const int t0 = 16 * s + 2 * q;
          const uint32_t m0 = (t0 < nvalid ? 0x3F80u : 0u) | (t0 + 1 < nvalid ? 0x3F800000u : 0u);
          const uint32_t m1 = (t0 + 8 < nvalid ? 0x3F80u : 0u) | (t0 + 9 < nvalid ? 0x3F800000u : 0u);
#pragma unroll
          for (int h2 = 0; h2 < 2; h2++) {
            const uint32_t b0 = p[4 * s + h2], b1 = s < 4 ? p[(4 * s + 2 + h2) % 18] : 0u;
            mma16816(dkv[h2], pv[4 * s], pv[4 * s + 1], s < 4 ? pv[(4 * s + 2) % 18] : 0u, s < 4 ? pv[(4 * s + 3) % 18] : 0u, b0, b1);
            mma16816(dz[h2], m0, m0, m1, m1, b0, b1);
          }
        }
        asm volatile("bar.sync %0, 160;" ::"r"(12 + w) : "memory");
        unsigned epoch;
        asm volatile("ld.shared.u32 %0, [%1];" : "=r"(epoch) : "r"(sb + OFF_EPOCH) : "memory");
        float* kvg = &g_kv[epoch & 1][(4 * j + w4) * 272];
#pragma unroll
        for (int h2 = 0; h2 < 2; h2++) {
          red_add_v2(kvg + g * 16 + 8 * h2 + 2 * q, dkv[h2][0], dkv[h2][1]);
          red_add_v2(kvg + (g + 8) * 16 + 8 * h2 + 2 * q, dkv[h2][2], dkv[h2][3]);
          if (g == 0) red_add_v2(kvg + 256 + 8 * h2 + 2 * q, dz[h2][0], dz[h2][1]);
        }
        __syncwarp();
        mbar_arrive_pred(sb + BAR_KVDONE, 1, lane == 0);
      } else {
        if (t == 1) {
#pragma unroll
          for (int i = 0; i < 18; i++) p[i] = movmat(p[i]);
          TS(8);
          mbar_wait(sb + BAR_KVRDY, 0);
          TS(9);
          unsigned epoch;
          asm volatile("ld.shared.u32 %0, [%1];" : "=r"(epoch) : "r"(sb + OFF_EPOCH) : "memory");
          const float* kb = &g_kv[epoch & 1][(4 * j + w4) * 272];
          const float2 f0 = ld_relaxed_v2(kb + g * 16 + 2 * q), f1 = ld_relaxed_v2(kb + (g + 8) * 16 + 2 * q);
          const float2 f2 = ld_relaxed_v2(kb + g * 16 + 8 + 2 * q), f3 = ld_relaxed_v2(kb + (g + 8) * 16 + 8 + 2 * q);
          const float2 z0 = ld_relaxed_v2(kb + 256 + 2 * q), z1 = ld_relaxed_v2(kb + 256 + 8 + 2 * q);
          const uint32_t a0 = pack_bf16(f0.x, f0.y), a1 = pack_bf16(f1.x, f1.y), a2 = pack_bf16(f2.x, f2.y), a3 = pack_bf16(f3.x, f3.y);
          const uint32_t zz0 = pack_bf16(z0.x, z0.y), zz1 = pack_bf16(z1.x, z1.y);
#pragma unroll
          for (int jj = 0; jj < 9; jj++) {
            float num[4] = {}, den[4] = {};
            mma16816(num, a0, a1, a2, a3, p[2 * jj], p[2 * jj + 1]);
            mma16816(den, zz0, zz0, zz1, zz1, p[2 * jj], p[2 * jj + 1]);
            const float r0 = __fdividef(1.f, den[0] + 1e-6f), r1 = __fdividef(1.f, den[1] + 1e-6f);
            p[2 * jj] = pack_bf16(num[0] * r0, num[1] * r1);
            p[2 * jj + 1] = pack_bf16(num[2] * r0, num[3] * r1);
          }
        }
        const uint32_t a = act0 + j * SLOT_BYTES + w * HALF_BYTES + loff;
        stage_frag(a, tail_ok ? a + 8 * 1024 : sb + OFF_DUMMY, p);
        mbar_arrive_pred(sb + BAR_PUB + 8 * (t == 3 ? 5 : t - 1), 1, lane == 0);
      }
      TS(16 + (t == 3 ? 7 : t + 1));
    }
  }
}

typedef CUresult (*EncodeFn)(CUtensorMap*, CUtensorMapDataType, cuuint32_t, void*, const cuuint64_t*, const cuuint64_t*,
                             const cuuint32_t*, const cuuint32_t*, CUtensorMapInterleave, CUtensorMapSwizzle,
                             CUtensorMapL2promotion, CUtensorMapFloatOOBfill);

void make_map(EncodeFn enc, CUtensorMap* m, const void* base, int rows, int cols, int box_rows) {
  cuuint64_t dims[2] = {(cuuint64_t)cols, (cuuint64_t)rows};
  cuuint64_t strides[1] = {(cuuint64_t)cols * 2};
  cuuint32_t box[2] = {64, (cuuint32_t)box_rows};
  cuuint32_t es[2] = {1, 1};
  enc(m, CU_TENSOR_MAP_DATA_TYPE_BFLOAT16, 2, const_cast<void*>(base), dims, strides, box, es, CU_TENSOR_MAP_INTERLEAVE_NONE,
      CU_TENSOR_MAP_SWIZZLE_128B, CU_TENSOR_MAP_L2_PROMOTION_L2_128B, CU_TENSOR_MAP_FLOAT_OOB_FILL_NONE);
}

}

extern "C" void kernel_launch(void* const* d_in, const int* in_sizes, int n_in, void* d_out, int out_size) {
  (void)in_sizes; (void)n_in; (void)out_size;
  static EncodeFn enc = nullptr;
  static void* pscr = nullptr;
  if (!enc) {
    void* fn = nullptr;
    cudaDriverEntryPointQueryResult qr;
    cudaGetDriverEntryPoint("cuTensorMapEncodeTiled", &fn, cudaEnableDefault, &qr);
    enc = (EncodeFn)fn;
    cudaGetSymbolAddress(&pscr, g_scr);
    cudaFuncSetAttribute(fused_kernel, cudaFuncAttributeMaxDynamicSharedMemorySize, SMEM_ALLOC);
  }
  Params P;
  make_map(enc, &P.x, d_in[0], S_TOK, DM, TH);
  make_map(enc, &P.wqkv, d_in[1], DM, 3 * DM, 64);
  make_map(enc, &P.wo, d_in[2], DM, DM, 64);
  make_map(enc, &P.wg, d_in[4], DM, FF, 64);
  make_map(enc, &P.wu, d_in[5], DM, FF, 64);
  make_map(enc, &P.wd, d_in[6], FF, DM, 64);
  make_map(enc, &P.scr, pscr, NCL * SCR_TILES * TOKC, 64, TH);
  make_map(enc, &P.out, d_out, S_TOK, DM, TH);
  P.p_x = (const __nv_bfloat16*)d_in[0];
  P.p_wqkv = (const __nv_bfloat16*)d_in[1];
  P.p_wo = (const __nv_bfloat16*)d_in[2];
  P.p_wg = (const __nv_bfloat16*)d_in[4];
  P.p_wu = (const __nv_bfloat16*)d_in[5];
  P.p_wd = (const __nv_bfloat16*)d_in[6];
  P.p_scr = (__nv_bfloat16*)pscr;

  cudaLaunchConfig_t cfg = {};
  cfg.gridDim = dim3(NCL * CL);
  cfg.blockDim = dim3(384);
  cfg.dynamicSmemBytes = SMEM_ALLOC;
  cfg.stream = cudaStreamPerThread;
  cudaLaunchAttribute at[1];
  at[0].id = cudaLaunchAttributeClusterDimension;
  at[0].val.clusterDim.x = CL;
  at[0].val.clusterDim.y = 1;
  at[0].val.clusterDim.z = 1;
  cfg.attrs = at;
  cfg.numAttrs = 1;
  cudaLaunchKernelEx(&cfg, fused_kernel, P);
}
```

```cpp
#include <cuda_runtime.h>
#include <cuda_bf16.h>
#include <cuda.h>
#include <stdint.h>

namespace {

constexpr int S_TOK = 2048, DM = 512, FF = 1376;
constexpr int CL = 8, NCL = 15;
constexpr int TH = 69;
constexpr int TOKC = 2 * TH;
constexpr int SLOT_BYTES = 144 * 128;
constexpr int HALF_BYTES = 72 * 128;
constexpr int BOX_BYTES = TH * 128;
constexpr int TILE_TX = 2 * BOX_BYTES;
constexpr int WST = 5;
constexpr int WST_BYTES = 128 * 128;
constexpr int NFT = 22;

constexpr int OFF_ACT = 0;
constexpr int OFF_RING = 8 * SLOT_BYTES;
constexpr int OFF_STAT = OFF_RING + WST * WST_BYTES;
constexpr int OFF_BAR = OFF_STAT + 144 * 8;
constexpr int BAR_WFULL = OFF_BAR;
constexpr int BAR_WEMPTY = BAR_WFULL + WST * 8;
constexpr int BAR_AFULL = BAR_WEMPTY + WST * 8;
constexpr int BAR_AEMPTY = BAR_AFULL + 64;
constexpr int BAR_STAT = BAR_AEMPTY + 8;
constexpr int BAR_KVDONE = BAR_STAT + 8;
constexpr int BAR_KVRDY = BAR_KVDONE + 8;
constexpr int BAR_PUB = BAR_KVRDY + 8;
constexpr int BAR_VIS = BAR_PUB + 6 * 8;
constexpr int NBAR = 2 * WST + 8 + 4 + 6 + 5;
constexpr int OFF_EPOCH = BAR_VIS + 5 * 8;
constexpr int OFF_DUMMY = (OFF_EPOCH + 4 + 15) & ~15;
constexpr int SMEM_ALLOC = OFF_DUMMY + 16;
static_assert(SMEM_ALLOC <= 232448, "shared memory budget");

struct alignas(64) Params {
  CUtensorMap x, wqkv, wo, wg, wu, wd, scr, out;
  const __nv_bfloat16 *p_x, *p_wqkv, *p_wo, *p_wg, *p_wu, *p_wd;
  __nv_bfloat16* p_scr;
};

constexpr int SCR_TILES = 16 + NFT;
__device__ __align__(1024) __nv_bfloat16 g_scr[NCL * SCR_TILES * TOKC * 64];
__device__ __align__(128) float g_kv[2][32 * 272];
__device__ __align__(128) unsigned g_flag[8 * 32];
__device__ unsigned g_epoch;

__device__ __forceinline__ uint32_t smem_u32(const void* p) { return (uint32_t)__cvta_generic_to_shared(p); }
__device__ __forceinline__ void mbar_init(uint32_t bar, uint32_t cnt) {
  asm volatile("mbarrier.init.shared::cta.b64 [%0], %1;" ::"r"(bar), "r"(cnt) : "memory");
}
__device__ __forceinline__ void mbar_expect_tx(uint32_t bar, uint32_t bytes) {
  asm volatile("mbarrier.arrive.expect_tx.shared::cta.b64 _, [%0], %1;" ::"r"(bar), "r"(bytes) : "memory");
}
__device__ __forceinline__ void mbar_arrive(uint32_t bar) {
  asm volatile("mbarrier.arrive.shared::cta.b64 _, [%0];" ::"r"(bar) : "memory");
}
__device__ __forceinline__ uint32_t mapa(uint32_t addr, uint32_t cta) {
  uint32_t r;
  asm volatile("mapa.shared::cluster.u32 %0, %1, %2;" : "=r"(r) : "r"(addr), "r"(cta));
  return r;
}
constexpr int SPIN_LIMIT = 1 << 18;
__device__ __forceinline__ void mbar_wait(uint32_t bar, uint32_t parity) {
  uint32_t done;
  int it = 0;
  do {
    asm volatile(
        "{ .reg .pred p; mbarrier.try_wait.parity.shared::cta.b64 p, [%1], %2; selp.u32 %0, 1, 0, p; }"
        : "=r"(done) : "r"(bar), "r"(parity) : "memory");
  } while (!done && ++it < SPIN_LIMIT);
}
__device__ __forceinline__ void mbar_wait2(uint32_t bar0, uint32_t par0, uint32_t bar1, uint32_t par1) {
  uint32_t done;
  int it = 0;
  do {
    asm volatile(
        "{ .reg .pred p, q;\n"
        "mbarrier.try_wait.parity.shared::cta.b64 p, [%1], %2;\n"
        "mbarrier.try_wait.parity.shared::cta.b64 q, [%3], %4;\n"
        "and.pred p, p, q;\n"
        "selp.u32 %0, 1, 0, p; }"
        : "=r"(done) : "r"(bar0), "r"(par0), "r"(bar1), "r"(par1) : "memory");
  } while (!done && ++it < SPIN_LIMIT);
}
__device__ __forceinline__ uint32_t mbar_peek3(uint32_t w0, uint32_t pw0, uint32_t a0, uint32_t a1, uint32_t pa) {
  uint32_t done;
  asm volatile(
      "{ .reg .pred p, r, s;\n"
      "mbarrier.test_wait.parity.shared::cta.b64 p, [%1], %2;\n"
      "mbarrier.test_wait.parity.shared::cta.b64 r, [%3], %5;\n"
      "mbarrier.test_wait.parity.shared::cta.b64 s, [%4], %5;\n"
      "and.pred r, r, s;\n"
      "and.pred p, p, r;\n"
      "selp.u32 %0, 1, 0, p; }"
      : "=r"(done) : "r"(w0), "r"(pw0), "r"(a0), "r"(a1), "r"(pa) : "memory");
  return done;
}
__device__ __forceinline__ void mbar_arrive_pred(uint32_t bar, uint32_t cnt, bool pred) {
  asm volatile("{ .reg .pred p; setp.ne.b32 p, %2, 0; @p mbarrier.arrive.shared::cta.b64 _, [%0], %1; }" ::"r"(bar), "r"(cnt), "r"((int)pred) : "memory");
}
__device__ __forceinline__ void mbar_expect_tx_pred(uint32_t bar, uint32_t bytes, bool pred) {
  asm volatile("{ .reg .pred p; setp.ne.b32 p, %2, 0; @p mbarrier.arrive.expect_tx.shared::cta.b64 _, [%0], %1; }" ::"r"(bar), "r"(bytes), "r"((int)pred) : "memory");
}
__device__ __forceinline__ void mbar_arrive_remote_pred(uint32_t bar, uint32_t cta, uint32_t cnt, bool pred) {
  asm volatile("{ .reg .pred p; .reg .b32 ra; setp.ne.b32 p, %2, 0; mapa.shared::cluster.u32 ra, %0, %1; @p mbarrier.arrive.shared::cluster.b64 _, [ra], %3; }" ::"r"(bar), "r"(cta), "r"((int)pred), "r"(cnt) : "memory");
}
__device__ __forceinline__ void st_async_v2(uint32_t raddr, float a, float b, uint32_t rbar) {
  asm volatile("st.async.weak.shared::cluster.mbarrier::complete_tx::bytes.v2.f32 [%0], {%1, %2}, [%3];" ::"r"(raddr), "f"(a), "f"(b),
               "r"(rbar) : "memory");
}
__device__ __forceinline__ float2 ld_relaxed_v2(const float* p) {
  float2 v;
  asm volatile("ld.relaxed.gpu.global.v2.f32 {%0, %1}, [%2];" : "=f"(v.x), "=f"(v.y) : "l"(p) : "memory");
  return v;
}
__device__ __forceinline__ void st_global_v2_pred(void* p, uint32_t a, uint32_t b, bool pred) {
  asm volatile("{ .reg .pred p; setp.ne.b32 p, %3, 0; @p st.global.v2.b32 [%0], {%1, %2}; }" ::"l"(p), "r"(a), "r"(b), "r"((int)pred) : "memory");
}
__device__ __forceinline__ void tma_load(uint32_t dst, const CUtensorMap* m, int c0, int c1, uint32_t bar) {
  asm volatile(
      "cp.async.bulk.tensor.2d.shared::cluster.global.mbarrier::complete_tx::bytes [%0], [%1, {%3, %4}], [%2];" ::"r"(dst),
      "l"(m), "r"(bar), "r"(c0), "r"(c1) : "memory");
}
__device__ __forceinline__ void tma_load_mc(uint32_t dst, const CUtensorMap* m, int c0, int c1, uint32_t bar) {
  asm volatile(
      "cp.async.bulk.tensor.2d.shared::cluster.global.mbarrier::complete_tx::bytes.multicast::cluster [%0], [%1, {%3, "
      "%4}], [%2], %5;" ::"r"(dst),
      "l"(m), "r"(bar), "r"(c0), "r"(c1), "h"((uint16_t)0xFF) : "memory");
}
__device__ __forceinline__ void tma_store(const CUtensorMap* m, int c0, int c1, uint32_t src) {
  asm volatile("cp.async.bulk.tensor.2d.global.shared::cta.bulk_group [%0, {%2, %3}], [%1];" ::"l"(m), "r"(src), "r"(c0),
               "r"(c1) : "memory");
}
__device__ __forceinline__ void bulk_commit() { asm volatile("cp.async.bulk.commit_group;" ::: "memory"); }
__device__ __forceinline__ void bulk_wait_all() { asm volatile("cp.async.bulk.wait_group 0;" ::: "memory"); }
__device__ __forceinline__ void bulk_wait_read() { asm volatile("cp.async.bulk.wait_group.read 0;" ::: "memory"); }
__device__ __forceinline__ void fence_async_smem() { asm volatile("fence.proxy.async.shared::cta;" ::: "memory"); }
__device__ __forceinline__ void prefetch_tmap(const CUtensorMap* m) {
  asm volatile("prefetch.tensormap [%0];" ::"l"(m) : "memory");
}
__device__ __forceinline__ void l2_prefetch(const void* p, uint32_t bytes) {
  asm volatile("cp.async.bulk.prefetch.L2.global [%0], %1;" ::"l"(p), "r"(bytes) : "memory");
}
#define WG_FENCE() asm volatile("wgmma.fence.sync.aligned;" ::: "memory")
#define WG_COMMIT() asm volatile("wgmma.commit_group.sync.aligned;" ::: "memory")
#define WG_WAIT(n) asm volatile("wgmma.wait_group.sync.aligned %0;" ::"n"(n) : "memory")
template <int N>
__device__ __forceinline__ void fence_acc(float (&d)[N]) {
#pragma unroll
  for (int i = 0; i < N; i++) asm volatile("" : "+f"(d[i])::"memory");
}
constexpr uint32_t DESC_HI = 0x40000000u | (1024 >> 4);
__device__ __forceinline__ uint32_t mk_desc(uint32_t addr) { return ((addr & 0x3FFFF) >> 4) | (1u << 16); }

__device__ __forceinline__ void wgmma_n72(float (&d)[36], uint32_t da, uint32_t db, int scale_d) {
  asm volatile("{ .reg .pred p; .reg .b64 da, db; setp.ne.b32 p, %38, 0;\n"
    "mov.b64 da, {%36, %39}; mov.b64 db, {%37, %39};\n"
    "wgmma.mma_async.sync.aligned.m64n72k16.f32.bf16.bf16 {"
    "%0,%1,%2,%3,%4,%5,%6,%7,%8,%9,%10,%11,"
    "%12,%13,%14,%15,%16,%17,%18,%19,%20,%21,%22,%23,"
    "%24,%25,%26,%27,%28,%29,%30,%31,%32,%33,%34,%35"
    "}, da, db, p, 1, 1, 1, 0; }"
    : "+f"(d[0]), "+f"(d[1]), "+f"(d[2]), "+f"(d[3]), "+f"(d[4]), "+f"(d[5]), "+f"(d[6]), "+f"(d[7]),
      "+f"(d[8]), "+f"(d[9]), "+f"(d[10]), "+f"(d[11]), "+f"(d[12]), "+f"(d[13]), "+f"(d[14]), "+f"(d[15]),
      "+f"(d[16]), "+f"(d[17]), "+f"(d[18]), "+f"(d[19]), "+f"(d[20]), "+f"(d[21]), "+f"(d[22]), "+f"(d[23]),
      "+f"(d[24]), "+f"(d[25]), "+f"(d[26]), "+f"(d[27]), "+f"(d[28]), "+f"(d[29]), "+f"(d[30]), "+f"(d[31]),
      "+f"(d[32]), "+f"(d[33]), "+f"(d[34]), "+f"(d[35])
    : "r"(da), "r"(db), "r"(scale_d), "r"(DESC_HI));
}

__device__ __forceinline__ void wgmma_n144(float (&d)[72], uint32_t da, uint32_t db, int scale_d) {
  asm volatile("{ .reg .pred p; .reg .b64 da, db; setp.ne.b32 p, %74, 0;\n"
    "mov.b64 da, {%72, %75}; mov.b64 db, {%73, %75};\n"
    "wgmma.mma_async.sync.aligned.m64n144k16.f32.bf16.bf16 {"
    "%0,%1,%2,%3,%4,%5,%6,%7,%8,%9,%10,%11,"
    "%12,%13,%14,%15,%16,%17,%18,%19,%20,%21,%22,%23,"
    "%24,%25,%26,%27,%28,%29,%30,%31,%32,%33,%34,%35,"
    "%36,%37,%38,%39,%40,%41,%42,%43,%44,%45,%46,%47,"
    "%48,%49,%50,%51,%52,%53,%54,%55,%56,%57,%58,%59,"
    "%60,%61,%62,%63,%64,%65,%66,%67,%68,%69,%70,%71"
    "}, da, db, p, 1, 1, 1, 0; }"
    : "+f"(d[0]), "+f"(d[1]), "+f"(d[2]), "+f"(d[3]), "+f"(d[4]), "+f"(d[5]), "+f"(d[6]), "+f"(d[7]),
      "+f"(d[8]), "+f"(d[9]), "+f"(d[10]), "+f"(d[11]), "+f"(d[12]), "+f"(d[13]), "+f"(d[14]), "+f"(d[15]),
      "+f"(d[16]), "+f"(d[17]), "+f"(d[18]), "+f"(d[19]), "+f"(d[20]), "+f"(d[21]), "+f"(d[22]), "+f"(d[23]),
      "+f"(d[24]), "+f"(d[25]), "+f"(d[26]), "+f"(d[27]), "+f"(d[28]), "+f"(d[29]), "+f"(d[30]), "+f"(d[31]),
      "+f"(d[32]), "+f"(d[33]), "+f"(d[34]), "+f"(d[35]), "+f"(d[36]), "+f"(d[37]), "+f"(d[38]), "+f"(d[39]),
      "+f"(d[40]), "+f"(d[41]), "+f"(d[42]), "+f"(d[43]), "+f"(d[44]), "+f"(d[45]), "+f"(d[46]), "+f"(d[47]),
      "+f"(d[48]), "+f"(d[49]), "+f"(d[50]), "+f"(d[51]), "+f"(d[52]), "+f"(d[53]), "+f"(d[54]), "+f"(d[55]),
      "+f"(d[56]), "+f"(d[57]), "+f"(d[58]), "+f"(d[59]), "+f"(d[60]), "+f"(d[61]), "+f"(d[62]), "+f"(d[63]),
      "+f"(d[64]), "+f"(d[65]), "+f"(d[66]), "+f"(d[67]), "+f"(d[68]), "+f"(d[69]), "+f"(d[70]), "+f"(d[71])
    : "r"(da), "r"(db), "r"(scale_d), "r"(DESC_HI));
}

__device__ __forceinline__ void mma16816(float (&c)[4], uint32_t a0, uint32_t a1, uint32_t a2, uint32_t a3, uint32_t b0,
                                         uint32_t b1) {
  asm volatile(
      "mma.sync.aligned.m16n8k16.row.col.f32.bf16.bf16.f32 {%0,%1,%2,%3}, {%4,%5,%6,%7}, {%8,%9}, {%0,%1,%2,%3};"
      : "+f"(c[0]), "+f"(c[1]), "+f"(c[2]), "+f"(c[3])
      : "r"(a0), "r"(a1), "r"(a2), "r"(a3), "r"(b0), "r"(b1));
}
__device__ __forceinline__ uint32_t movmat(uint32_t a) {
  uint32_t d;
  asm volatile("movmatrix.sync.aligned.m8n8.trans.b16 %0, %1;" : "=r"(d) : "r"(a));
  return d;
}
__device__ __forceinline__ void stsm4t(uint32_t addr, uint32_t r0, uint32_t r1, uint32_t r2, uint32_t r3) {
  asm volatile("stmatrix.sync.aligned.m8n8.x4.trans.shared.b16 [%0], {%1,%2,%3,%4};" ::"r"(addr), "r"(r0), "r"(r1),
               "r"(r2), "r"(r3) : "memory");
}
__device__ __forceinline__ void stsm2t(uint32_t addr, uint32_t r0, uint32_t r1) {
  asm volatile("stmatrix.sync.aligned.m8n8.x2.trans.shared.b16 [%0], {%1,%2};" ::"r"(addr), "r"(r0), "r"(r1) : "memory");
}
__device__ __forceinline__ void ldsm4t(uint32_t addr, uint32_t& r0, uint32_t& r1, uint32_t& r2, uint32_t& r3) {
  asm volatile("ldmatrix.sync.aligned.m8n8.x4.trans.shared.b16 {%0,%1,%2,%3}, [%4];"
               : "=r"(r0), "=r"(r1), "=r"(r2), "=r"(r3) : "r"(addr) : "memory");
}
__device__ __forceinline__ void ldsm2t(uint32_t addr, uint32_t& r0, uint32_t& r1) {
  asm volatile("ldmatrix.sync.aligned.m8n8.x2.trans.shared.b16 {%0,%1}, [%2];" : "=r"(r0), "=r"(r1) : "r"(addr) : "memory");
}
__device__ __forceinline__ float4 lds128f(uint32_t addr) {
  float4 v;
  asm volatile("ld.shared.v4.f32 {%0,%1,%2,%3}, [%4];" : "=f"(v.x), "=f"(v.y), "=f"(v.z), "=f"(v.w) : "r"(addr) : "memory");
  return v;
}
__device__ __forceinline__ uint4 lds128u(uint32_t addr) {
  uint4 v;
  asm volatile("ld.shared.v4.u32 {%0,%1,%2,%3}, [%4];" : "=r"(v.x), "=r"(v.y), "=r"(v.z), "=r"(v.w) : "r"(addr) : "memory");
  return v;
}
__device__ __forceinline__ uint32_t pack_bf16(float lo, float hi) {
  uint32_t r;
  asm("cvt.rn.bf16x2.f32 %0, %1, %2;" : "=r"(r) : "f"(hi), "f"(lo));
  return r;
}
__device__ __forceinline__ float bf_lo(uint32_t p) { return __uint_as_float(p << 16); }
__device__ __forceinline__ float bf_hi(uint32_t p) { return __uint_as_float(p & 0xFFFF0000u); }
__device__ __forceinline__ float ex2(float t) {
  float r;
  asm("ex2.approx.ftz.f32 %0, %1;" : "=f"(r) : "f"(t));
  return r;
}
__device__ __forceinline__ void red_add_v2(float* p, float a, float b) {
  asm volatile("red.relaxed.gpu.global.add.v2.f32 [%0], {%1, %2};" ::"l"(p), "f"(a), "f"(b) : "memory");
}

template <int N>
__device__ __forceinline__ void wgmma(float (&d)[N / 2], uint32_t da, uint32_t db, int scale_d) {
  if constexpr (N == 144) wgmma_n144(d, da, db, scale_d);
  else wgmma_n72(d, da, db, scale_d);
}

struct Ring {
  int ws, ph;
  __device__ __forceinline__ void advance() { if (++ws == WST) { ws = 0; ph ^= 1; } }
};

template <int N, bool SAME>
__device__ __forceinline__ void mma_loop(float (&accA)[N / 2], float (&accB)[N / 2], Ring& R, uint32_t sb, uint32_t actB, int n,
                                         int par0, int parmask, uint32_t relcnt, int relsteps, int keepslot, bool arm, int t128, int sigbar) {
  const uint32_t wlo = mk_desc(sb + OFF_RING), alo = mk_desc(actB);
  const bool lead = t128 == 0, lead2 = t128 < (SAME ? 2 : 1);
  const uint32_t l = SAME ? (t128 & 1) : 0;
  auto release = [&](int i, int stage) {
    mbar_arrive_pred(sb + BAR_WEMPTY + 8 * stage, relcnt, lead);
    const uint32_t sl = (SAME ? ((2 * i) & 7) : i) + l;
    const bool mine = (i < relsteps) && lead2 && (int)sl != keepslot;
    mbar_expect_tx_pred(sb + BAR_AFULL + 8 * sl, TILE_TX, mine && arm);
    mbar_arrive_remote_pred(sb + BAR_AEMPTY, sl, (N == 144 && SAME) ? 2 : 1, mine);
  };
  uint32_t tok = 0;
  int prev = 0;
#pragma unroll 1
  for (int i = 0; i < n; i++) {
    const int ws = R.ws;
    const int a = SAME ? ((2 * i) & 7) : i;
    if (!tok) {
      const int pa = (par0 + ((i >> 2) & parmask)) & 1;
      mbar_wait(sb + BAR_WFULL + 8 * ws, R.ph);
      mbar_wait2(sb + BAR_AFULL + 8 * a, pa, sb + BAR_AFULL + 8 * a + (SAME ? 8 : 0), pa);
    }
    R.advance();
    const uint32_t da = wlo + ws * (WST_BYTES >> 4), db = alo + a * (SLOT_BYTES >> 4);
    WG_FENCE();
#pragma unroll
    for (int kk = 0; kk < 3; kk++) wgmma<N>(accA, da + kk * 128, db + kk * 2, 1);
    WG_COMMIT();
    const int i1 = i + 1, a1 = SAME ? ((2 * i1) & 7) : (i1 & 7);
    tok = mbar_peek3(sb + BAR_WFULL + 8 * R.ws, R.ph, sb + BAR_AFULL + 8 * a1, sb + BAR_AFULL + 8 * a1 + (SAME ? 8 : 0),
                     (par0 + ((i1 >> 2) & parmask)) & 1);
    if (sigbar && i == n - 1) asm volatile("bar.arrive %0, 256;" ::"r"(sigbar) : "memory");
    WG_WAIT(1);
    if (i > 0) release(i - 1, prev);
    prev = ws;
    wgmma<N>(accA, da + 384, db + 6, 1);
    if constexpr (SAME) {
#pragma unroll
      for (int kk = 0; kk < 4; kk++) wgmma<N>(accA, da + 512 + kk * 128, db + (SLOT_BYTES >> 4) + kk * 2, 1);
    } else {
#pragma unroll
      for (int kk = 0; kk < 4; kk++) wgmma<N>(accB, da + 512 + kk * 128, db + kk * 2, 1);
    }
    WG_COMMIT();
  }
  WG_WAIT(0);
  fence_acc(accA);
  if constexpr (!SAME) fence_acc(accB);
  release(n - 1, prev);
}

__device__ __forceinline__ void stage_frag(uint32_t a, uint32_t a8, const uint32_t (&p)[18]) {
#pragma unroll
  for (int jj = 0; jj < 8; jj += 2) stsm4t(a + jj * 1024, p[2 * jj], p[2 * jj + 1], p[2 * jj + 2], p[2 * jj + 3]);
  stsm2t(a8, p[16], p[17]);
  fence_async_smem();
  __syncwarp();
}
__device__ __forceinline__ void load_frag(uint32_t a, uint32_t (&p)[18]) {
#pragma unroll
  for (int jj = 0; jj < 8; jj += 2) ldsm4t(a + jj * 1024, p[2 * jj], p[2 * jj + 1], p[2 * jj + 2], p[2 * jj + 3]);
  ldsm2t(a + 8 * 1024, p[16], p[17]);
}
__device__ __forceinline__ void store_frag(char* d, const uint32_t (&p)[18], int q) {
#pragma unroll
  for (int jj = 0; jj < 9; jj++) {
    const uint32_t lo = movmat(p[2 * jj]), hi = movmat(p[2 * jj + 1]);
    const uint32_t recv = __shfl_xor_sync(0xffffffffu, (q & 1) ? lo : hi, 1);
    st_global_v2_pred(d + jj * 1024, (q & 1) ? recv : lo, (q & 1) ? hi : recv, jj < 8 || (threadIdx.x & 31) < 4 * (TH - 64));
  }
}

__global__ void __launch_bounds__(384, 1) fused_kernel(const __grid_constant__ Params P) {
  extern __shared__ __align__(1024) uint8_t smem_raw[];
  const uint32_t sb = smem_u32(smem_raw);
  const int tid = threadIdx.x, warp = __shfl_sync(0xffffffffu, tid >> 5, 0), lane = tid & 31;
  uint32_t rank;
  asm volatile("mov.u32 %0, %%cluster_ctarank;" : "=r"(rank));
  const int j = (int)rank;
  const int cl = blockIdx.x / CL;
  const int tok0 = cl * TOKC;
  const int nr = (j + 16 < NFT) ? 3 : 2;

  if (lane == 0) {
#pragma unroll 1
    for (int b = warp; b < NBAR; b += 12) {
      uint32_t cnt = 1;
      if (b >= WST && b < 2 * WST) cnt = 2;
      const int o = b - (2 * WST + 8);
      if (o == 0) cnt = 16;
      if (o == 2 || (o >= 4 && o < 10)) cnt = 8;
      mbar_init(sb + OFF_BAR + 8 * b, cnt);
    }
    asm volatile("fence.mbarrier_init.release.cluster;" ::: "memory");
  }
  __syncwarp();
  if (warp >= 8) {
    const int i = (tid - 256) * NCL + cl;
    if (i < 3 * DM) {
      const int part = i < 2 * DM ? 1 + (i & 1) : 0, row = i < 2 * DM ? (i >> 1) : i - 2 * DM;
      const char* wp = reinterpret_cast<const char*>(P.p_wqkv) + (size_t)row * (3 * DM * 2) + (512 * part + 64 * j) * 2;
      asm volatile("prefetch.global.L2 [%0];" ::"l"(wp) : "memory");
    }
    if (warp == 9 && lane < 8) prefetch_tmap(&P.x + lane);
  }
  uint4 v[5][2];
  if (warp >= 4 && warp < 8) {
#pragma unroll
    for (int i = 0; i < 5; i++) {
      const int row = 18 * j + min((warp & 3) + 4 * i, 17);
      const int tk = min(tok0 + row - (row >= 72 ? 3 : 0), S_TOK - 1);
      const uint4* src = reinterpret_cast<const uint4*>(P.p_x + (size_t)tk * DM) + lane;
      v[i][0] = __ldg(src);
      v[i][1] = __ldg(src + 32);
    }
  }
  if (warp < 4 && lane < 24) {
#pragma unroll
    for (int k = 0; k < 4; k++)
      asm volatile("st.shared.v4.u32 [%0], {%1,%1,%1,%1};" ::"r"(sb + OFF_ACT + (warp + 4 * k) * HALF_BYTES + 69 * 128 + lane * 16),
                   "r"(lane >= 16 ? 0x3F803F80u : 0u) : "memory");
    fence_async_smem();
  }
  __syncthreads();
  asm volatile("barrier.cluster.arrive.relaxed.aligned;" ::: "memory");

  if (warp >= 8) {
    if (lane == 0) {
      if (warp == 8) {
        mbar_expect_tx(sb + BAR_STAT, 144 * 8);
      } else if (warp == 9) {
#pragma unroll 1
        for (int n = 0; n < 3; n++) {
          const uint32_t dst = sb + OFF_RING + n * WST_BYTES, bar = sb + BAR_WFULL + 8 * n;
          mbar_expect_tx(bar, WST_BYTES);
          tma_load(dst, &P.wqkv, 64 * j + 512, 64 * n, bar);
          tma_load(dst + WST_BYTES / 2, &P.wqkv, 64 * j + 1024, 64 * n, bar);
        }
      } else if (warp > 9) {
#pragma unroll 1
        for (int s = warp - 10; s < 8; s += 2) {
          mbar_expect_tx(sb + BAR_AFULL + 8 * s, TILE_TX);
          tma_load(sb + OFF_ACT + s * SLOT_BYTES, &P.x, 64 * s, tok0, sb + BAR_AFULL + 8 * s);
          tma_load(sb + OFF_ACT + s * SLOT_BYTES + HALF_BYTES, &P.x, 64 * s, tok0 + TH, sb + BAR_AFULL + 8 * s);
        }
      }
    }
    __syncwarp();
    asm volatile("setmaxnreg.dec.sync.aligned.u32 40;");
    if (warp == 8) {
      if (lane == 0) {
        const int nstage = 16 + 8 * nr + NFT / 2;
        int st = 3, ph = 1;
#pragma unroll 1
        for (int n = 3; n < nstage; n++) {
          const uint32_t dst = sb + OFF_RING + st * WST_BYTES, bar = sb + BAR_WFULL + 8 * st;
          if (n >= WST) mbar_wait(sb + BAR_WEMPTY + 8 * st, ph);
          if (++st == WST) { st = 0; ph ^= 1; }
          mbar_expect_tx(bar, WST_BYTES);
          const CUtensorMap *m0, *m1;
          int c0 = 64 * j, c1 = c0, r0, r1;
          if (n < 8) { m0 = m1 = &P.wqkv; c0 += 512; c1 += 1024; r0 = r1 = 64 * n; }
          else if (n < 16) { m0 = m1 = n < 12 ? &P.wqkv : &P.wo; r0 = 128 * (n & 3); r1 = r0 + 64; }
          else if (n < 16 + 8 * nr) { m0 = &P.wg; m1 = &P.wu; c0 += 512 * ((n - 16) >> 3); c1 = c0; r0 = r1 = 64 * (n & 7); }
          else { m0 = m1 = &P.wd; r0 = 128 * (n - 16 - 8 * nr); r1 = r0 + 64; }
          tma_load(dst, m0, c0, r0, bar);
          tma_load(dst + WST_BYTES / 2, m1, c1, r1, bar);
        }
      }
    } else if (warp == 9) {
      asm volatile("barrier.cluster.wait.acquire.aligned;" ::: "memory");
      if (lane == 0) {
        const uint32_t slot = sb + OFF_ACT + j * SLOT_BYTES, af = sb + BAR_AFULL + 8 * j;
#pragma unroll 1
        for (int e = 1; e < 3 + nr; e++) {
          const int row = (cl * SCR_TILES + 8 * (e - 1) + j) * TOKC;
          mbar_wait(sb + BAR_VIS + 8 * (e - 1), 0);
          asm volatile("fence.proxy.async.global;" ::: "memory");
          mbar_wait(sb + BAR_AEMPTY, (e - 1) & 1);
          tma_load_mc(slot, &P.scr, 0, row, af);
          tma_load_mc(slot + HALF_BYTES, &P.scr, 0, row + TH, af);
        }
      }
    } else if (warp == 10) {
      unsigned epoch = 0;
      if (lane == 0) asm volatile("ld.relaxed.gpu.global.u32 %0, [%1];" : "=r"(epoch) : "l"(&g_epoch) : "memory");
      epoch = __shfl_sync(0xffffffffu, epoch, 0);
      if (lane == 0) asm volatile("st.shared.u32 [%0], %1;" ::"r"(sb + OFF_EPOCH), "r"(epoch) : "memory");
      __syncwarp();
      asm volatile("bar.arrive 12, 160;" ::: "memory");
      asm volatile("bar.arrive 13, 160;" ::: "memory");
      if (cl == 0) {
        float* z = &g_kv[(epoch + 1) & 1][j * 4 * 272];
#pragma unroll 1
        for (int i = lane; i < 4 * 272; i += 32) z[i] = 0.f;
      }
      mbar_wait(sb + BAR_KVDONE, 0);
      const unsigned target = (epoch + 1u) * NCL;
      if (lane == 0) {
        asm volatile("fence.acq_rel.gpu;" ::: "memory");
        asm volatile("red.relaxed.gpu.global.add.u32 [%0], %1;" ::"l"(&g_flag[j * 32]), "r"(1u) : "memory");
        unsigned v;
        int n = 0;
        do {
          asm volatile("ld.acquire.gpu.global.u32 %0, [%1];" : "=r"(v) : "l"(&g_flag[j * 32]) : "memory");
        } while ((int)(v - target) < 0 && ++n < SPIN_LIMIT);
      }
      __syncwarp();
      if (lane == 0) mbar_arrive(sb + BAR_KVRDY);
      if (blockIdx.x == 0) {
        unsigned v2 = target;
        int n = 0;
        do {
          if (lane < 8) asm volatile("ld.acquire.gpu.global.u32 %0, [%1];" : "=r"(v2) : "l"(&g_flag[lane * 32]) : "memory");
        } while (__any_sync(0xffffffffu, (int)(v2 - target) < 0) && ++n < SPIN_LIMIT);
        if (lane == 0) asm volatile("st.relaxed.gpu.global.u32 [%0], %1;" ::"l"(&g_epoch), "r"(epoch + 1u) : "memory");
      }
    } else {
      mbar_wait(sb + BAR_AFULL + 8 * 7, 0);
      if (lane < 4) {
        const uint32_t total = lane == 0 ? 512u * 512u * 2u : 512u * 1376u * 2u;
        const uint32_t chunk = lane == 0 ? 4480u : 11776u;
        const char* base = (const char*)(lane == 0 ? P.p_wo : lane == 1 ? P.p_wg : lane == 2 ? P.p_wu : P.p_wd);
        const uint32_t off = blockIdx.x * chunk;
        if (off < total) l2_prefetch(base + off, min(chunk, total - off));
      }
      if (lane == 0) {
        const uint32_t slot = sb + OFF_ACT + j * SLOT_BYTES;
#pragma unroll 1
        for (int e = 0; e < 3 + nr; e++) {
          const bool last = (e == 2 + nr);
          mbar_wait(sb + BAR_PUB + 8 * (last ? 5 : e), 0);
          if (e < 2 || last) {
            const CUtensorMap* m = last ? &P.out : &P.scr;
            const int c0 = last ? 64 * j : 0, c1 = last ? tok0 : (cl * SCR_TILES + 8 * e + j) * TOKC;
            tma_store(m, c0, c1, slot);
            tma_store(m, c0, c1 + TH, slot + HALF_BYTES);
            bulk_commit();
            if (last) { bulk_wait_read(); break; }
            bulk_wait_all();
          } else {
            asm volatile("fence.acq_rel.gpu;" ::: "memory");
          }
          mbar_arrive(sb + BAR_VIS + 8 * e);
        }
      }
    }
  } else {
    asm volatile("setmaxnreg.inc.sync.aligned.u32 232;");
    const int w = warp >> 2, w4 = warp & 3;
    const uint32_t act0 = sb + OFF_ACT;
    const int tokw = tok0 + w * TH;
    Ring R = {0, 0};
    uint32_t hres[18];

#pragma unroll 1
    for (int t = 0; t < 4; t++) {
      int lane = tid & 31;
      asm volatile("" : "+r"(lane));
      const int g = lane >> 2, q = lane & 3, t128 = w4 * 32 + lane;
      const int nvalid = min(TH, S_TOK - tokw);
      const uint32_t loff = (uint32_t)((8 * (lane >> 4) + (lane & 7)) * 128 + (((2 * w4 + ((lane >> 3) & 1)) ^ (lane & 7)) << 4));
      const bool tail_ok = (lane & 7) < TH - 64;
      if (w == 1 && (t == 0 || t == 3)) {
        if (t == 3) {
#pragma unroll 1
          for (int s = 0; s < 8; s++) mbar_wait(sb + BAR_AFULL + 8 * s, 0);
#pragma unroll
          for (int i = 0; i < 5; i++) {
            const int row = 18 * j + min(w4 + 4 * i, 17);
            const uint32_t a = act0 + (lane >> 3) * SLOT_BYTES + row * 128 + (((lane & 7) ^ (row & 7)) << 4);
            v[i][0] = lds128u(a);
            v[i][1] = lds128u(a + 4 * SLOT_BYTES);
          }
        }
        float s1[5], s2[5], piv[5];
#pragma unroll
        for (int i = 0; i < 5; i++) {
          piv[i] = __shfl_sync(0xffffffffu, bf_lo(v[i][0].x), 0);
          s1[i] = 0.f; s2[i] = 0.f;
#pragma unroll
          for (int k = 0; k < 2; k++) {
            const uint32_t u[4] = {v[i][k].x, v[i][k].y, v[i][k].z, v[i][k].w};
#pragma unroll
            for (int e = 0; e < 4; e++) {
              const float d0 = bf_lo(u[e]) - piv[i], d1 = bf_hi(u[e]) - piv[i];
              s1[i] += d0 + d1;
              s2[i] = fmaf(d0, d0, fmaf(d1, d1, s2[i]));
            }
          }
        }
#pragma unroll
        for (int o = 1; o < 32; o <<= 1) {
#pragma unroll
          for (int i = 0; i < 5; i++) {
            s1[i] += __shfl_xor_sync(0xffffffffu, s1[i], o);
            s2[i] += __shfl_xor_sync(0xffffffffu, s2[i], o);
          }
        }
        if (t == 0) asm volatile("barrier.cluster.wait.acquire.aligned;" ::: "memory");
        if (lane < CL) {
          const uint32_t rstat = mapa(sb + OFF_STAT, lane), rbar = mapa(sb + BAR_STAT, lane);
#pragma unroll
          for (int i = 0; i < 5; i++) {
            const int row = 18 * j + w4 + 4 * i;
            const int hf = row >= 72, rr = row - 72 * hf;
            const float md = s1[i] * (1.f / DM);
            const float var = fmaxf(s2[i] * (1.f / DM) - md * md, 0.f);
            const bool valid = rr < TH && tok0 + hf * TH + rr < S_TOK;
            if (w4 + 4 * i < 18) st_async_v2(rstat + row * 8, piv[i] + md, valid ? rsqrtf(var + 1e-5f) : 0.f, rbar);
          }
        }
      } else if (t == 0) {
        asm volatile("barrier.cluster.wait.acquire.aligned;" ::: "memory");
      }
#pragma unroll
      for (int i = 0; i < 5; i++) v[i][0] = v[i][1] = make_uint4(0u, 0u, 0u, 0u);
      auto fetch_res = [&]() {
        mbar_wait(sb + BAR_AFULL + 8 * j, 0);
        load_frag(act0 + j * SLOT_BYTES + w * HALF_BYTES + loff, hres);
      };
      if (t == 3) {
        const int wd = nr & 1;
        float accA[72], accB[72];
#pragma unroll 1
        for (int r = 0; r < nr; r++) {
          if ((r & 1) != w) {
            if (r == nr - 1) {
#pragma unroll
              for (int hf = 0; hf < 2; hf++) {
                uint32_t hr[18];
                load_frag(act0 + j * SLOT_BYTES + hf * HALF_BYTES + loff, hr);
#pragma unroll
                for (int i = 0; i < 18; i++) {
                  accB[36 * hf + (i >> 1) * 4 + (i & 1) * 2] = bf_lo(hr[i]);
                  accB[36 * hf + (i >> 1) * 4 + (i & 1) * 2 + 1] = bf_hi(hr[i]);
                }
              }
              asm volatile("bar.sync %0, 128;" ::"r"(8 + w) : "memory");
              mbar_expect_tx_pred(sb + BAR_AFULL + 8 * j, TILE_TX, t128 == 0 && w == 0);
              mbar_arrive_pred(sb + BAR_AEMPTY, 1, t128 == 0);
            }
            asm volatile("bar.sync %0, 256;" ::"r"(2 + r) : "memory");
#pragma unroll 1
            for (int i = 0; i < 8; i++) R.advance();
            continue;
          }
          const bool lastread = (r + 2 >= nr);
#pragma unroll
          for (int i = 0; i < 72; i++) { accA[i] = 0.f; accB[i] = 0.f; }
          mma_loop<144, false>(accA, accB, R, sb, act0, 8, 0, 0, 2, lastread ? 8 : 0, w == wd ? j : -1, w == 0, t128, 2 + r);
          mbar_wait(sb + BAR_STAT, 1);
#pragma unroll 1
          for (int hf = 0; hf < 2; hf++) {
            const float a0 = __shfl_sync(0xffffffffu, accA[33], lane | 3), a1 = __shfl_sync(0xffffffffu, accA[35], lane | 3);
            const float b0 = __shfl_sync(0xffffffffu, accB[33], lane | 3), b1 = __shfl_sync(0xffffffffu, accB[35], lane | 3);
            uint32_t p[18];
            float4 sts[9];
#pragma unroll
            for (int jj = 0; jj < 9; jj++) sts[jj] = lds128f(sb + OFF_STAT + (72 * hf + 8 * jj + 2 * q) * 8);
#pragma unroll
            for (int jj = 0; jj < 9; jj++) {
              const float4 st = sts[jj];
              const float r0 = st.y * st.y, r1 = st.w * st.w;
              p[2 * jj] = pack_bf16(r0 * (fmaf(-st.x, a0, accA[4 * jj]) * fmaf(-st.x, b0, accB[4 * jj])),
                                    r1 * (fmaf(-st.z, a0, accA[4 * jj + 1]) * fmaf(-st.z, b0, accB[4 * jj + 1])));
              p[2 * jj + 1] = pack_bf16(r0 * (fmaf(-st.x, a1, accA[4 * jj + 2]) * fmaf(-st.x, b1, accB[4 * jj + 2])),
                                        r1 * (fmaf(-st.z, a1, accA[4 * jj + 3]) * fmaf(-st.z, b1, accB[4 * jj + 3])));
            }
            store_frag(reinterpret_cast<char*>(P.p_scr) + (size_t)((cl * SCR_TILES + 16 + 8 * r + j) * TOKC + hf * TH + g) * 128 +
                           (16 * w4 + (q & 1) * 8 + (q >> 1) * 4) * 2, p, q);
#pragma unroll
            for (int i = 0; i < 36; i++) { accA[i] = accA[i + 36]; accB[i] = accB[i + 36]; }
          }
          __syncwarp();
          mbar_arrive_pred(sb + BAR_PUB + 8 * (2 + r), 2, lane == 0);
        }
        if (w == wd) {
          float accD[72];
#pragma unroll
          for (int i = 0; i < 72; i++) accD[i] = accB[i];
          fence_acc(accD);
          mma_loop<144, true>(accD, accD, R, sb, act0, NFT / 2, 3, 3, 2, (NFT - 8) / 2, -1, true, t128, 0);
#pragma unroll
          for (int hf = 0; hf < 2; hf++) {
            uint32_t p[18];
#pragma unroll
            for (int i = 0; i < 18; i++)
              p[i] = pack_bf16(accD[36 * hf + (i >> 1) * 4 + (i & 1) * 2], accD[36 * hf + (i >> 1) * 4 + (i & 1) * 2 + 1]);
            const uint32_t a = act0 + j * SLOT_BYTES + hf * HALF_BYTES + loff;
            stage_frag(a, tail_ok ? a + 8 * 1024 : sb + OFF_DUMMY, p);
          }
          mbar_arrive_pred(sb + BAR_PUB + 8 * 5, 2, lane == 0);
        }
        break;
      }
      if (t == 1) fetch_res();
      float acc[36];
      uint32_t pv[18];
      if (t == 2) {
#pragma unroll
        for (int i = 0; i < 18; i++) {
          acc[(i >> 1) * 4 + (i & 1) * 2] = bf_lo(hres[i]);
          acc[(i >> 1) * 4 + (i & 1) * 2 + 1] = bf_hi(hres[i]);
        }
      } else {
#pragma unroll
        for (int i = 0; i < 36; i++) acc[i] = 0.f;
      }
      auto load_stats = [&](float4 (&st)[9]) {
#pragma unroll
        for (int jj = 0; jj < 9; jj++) st[jj] = lds128f(sb + OFF_STAT + (72 * w + 8 * jj + 2 * q) * 8);
      };
      if (t == 0) {
        float av[36];
#pragma unroll
        for (int i = 0; i < 36; i++) av[i] = 0.f;
        mma_loop<72, false>(acc, av, R, sb, act0 + w * HALF_BYTES, 8, 0, 0, 1, 0, -1, w == 0, t128, 0);
        mbar_wait(sb + BAR_STAT, 0);
        mbar_expect_tx_pred(sb + BAR_STAT, 144 * 8, tid == 0);
        const float c0 = __shfl_sync(0xffffffffu, av[33], lane | 3), c1 = __shfl_sync(0xffffffffu, av[35], lane | 3);
        float4 st[9];
        load_stats(st);
#pragma unroll
        for (int jj = 0; jj < 9; jj++) {
          pv[2 * jj] = pack_bf16(st[jj].y * fmaf(-st[jj].x, c0, av[4 * jj]), st[jj].w * fmaf(-st[jj].z, c0, av[4 * jj + 1]));
          pv[2 * jj + 1] = pack_bf16(st[jj].y * fmaf(-st[jj].x, c1, av[4 * jj + 2]), st[jj].w * fmaf(-st[jj].z, c1, av[4 * jj + 3]));
        }
      } else {
        mma_loop<72, true>(acc, acc, R, sb, act0 + w * HALF_BYTES, 4, t - 1, 0, 1, 4, -1, w == 0, t128, 0);
      }
      uint32_t p[18];
      if (t < 2) {
        const float c0 = __shfl_sync(0xffffffffu, acc[33], lane | 3), c1 = __shfl_sync(0xffffffffu, acc[35], lane | 3);
        float4 st[9];
        load_stats(st);
#pragma unroll
        for (int i = 0; i < 36; i++) {
          const float m = (i & 1) ? st[i >> 2].z : st[i >> 2].x;
          const float rr = (i & 1) ? st[i >> 2].w : st[i >> 2].y;
          const float u = fmaf(-m, (i & 2) ? c1 : c0, acc[i]);
          const float tl = rr * 1.4426950408889634f * u;
          acc[i] = fmaxf(fmaf(rr, u, 1e-6f), 1e-6f) + ex2(fminf(tl, 0.f));
        }
      }
#pragma unroll
      for (int i = 0; i < 18; i++) p[i] = pack_bf16(acc[(i >> 1) * 4 + (i & 1) * 2], acc[(i >> 1) * 4 + (i & 1) * 2 + 1]);
      if (t == 0) {
        float dkv[2][4] = {}, dz[2][4] = {};
#pragma unroll
        for (int s = 0; s < 5; s++) {
          const int t0 = 16 * s + 2 * q;
          const uint32_t m0 = (t0 < nvalid ? 0x3F80u : 0u) | (t0 + 1 < nvalid ? 0x3F800000u : 0u);
          const uint32_t m1 = (t0 + 8 < nvalid ? 0x3F80u : 0u) | (t0 + 9 < nvalid ? 0x3F800000u : 0u);
#pragma unroll
          for (int h2 = 0; h2 < 2; h2++) {
            const uint32_t b0 = p[4 * s + h2], b1 = s < 4 ? p[(4 * s + 2 + h2) % 18] : 0u;
            mma16816(dkv[h2], pv[4 * s], pv[4 * s + 1], s < 4 ? pv[(4 * s + 2) % 18] : 0u, s < 4 ? pv[(4 * s + 3) % 18] : 0u, b0, b1);
            mma16816(dz[h2], m0, m0, m1, m1, b0, b1);
          }
        }
        asm volatile("bar.sync %0, 160;" ::"r"(12 + w) : "memory");
        unsigned epoch;
        asm volatile("ld.shared.u32 %0, [%1];" : "=r"(epoch) : "r"(sb + OFF_EPOCH) : "memory");
        float* kvg = &g_kv[epoch & 1][(4 * j + w4) * 272];
#pragma unroll
        for (int h2 = 0; h2 < 2; h2++) {
          red_add_v2(kvg + g * 16 + 8 * h2 + 2 * q, dkv[h2][0], dkv[h2][1]);
          red_add_v2(kvg + (g + 8) * 16 + 8 * h2 + 2 * q, dkv[h2][2], dkv[h2][3]);
          if (g == 0) red_add_v2(kvg + 256 + 8 * h2 + 2 * q, dz[h2][0], dz[h2][1]);
        }
        __syncwarp();
        mbar_arrive_pred(sb + BAR_KVDONE, 1, lane == 0);
      } else {
        if (t == 1) {
#pragma unroll
          for (int i = 0; i < 18; i++) p[i] = movmat(p[i]);
          mbar_wait(sb + BAR_KVRDY, 0);
          unsigned epoch;
          asm volatile("ld.shared.u32 %0, [%1];" : "=r"(epoch) : "r"(sb + OFF_EPOCH) : "memory");
          const float* kb = &g_kv[epoch & 1][(4 * j + w4) * 272];
          const float2 f0 = ld_relaxed_v2(kb + g * 16 + 2 * q), f1 = ld_relaxed_v2(kb + (g + 8) * 16 + 2 * q);
          const float2 f2 = ld_relaxed_v2(kb + g * 16 + 8 + 2 * q), f3 = ld_relaxed_v2(kb + (g + 8) * 16 + 8 + 2 * q);
          const float2 z0 = ld_relaxed_v2(kb + 256 + 2 * q), z1 = ld_relaxed_v2(kb + 256 + 8 + 2 * q);
          const uint32_t a0 = pack_bf16(f0.x, f0.y), a1 = pack_bf16(f1.x, f1.y), a2 = pack_bf16(f2.x, f2.y), a3 = pack_bf16(f3.x, f3.y);
          const uint32_t zz0 = pack_bf16(z0.x, z0.y), zz1 = pack_bf16(z1.x, z1.y);
#pragma unroll
          for (int jj = 0; jj < 9; jj++) {
            float num[4] = {}, den[4] = {};
            mma16816(num, a0, a1, a2, a3, p[2 * jj], p[2 * jj + 1]);
            mma16816(den, zz0, zz0, zz1, zz1, p[2 * jj], p[2 * jj + 1]);
            const float r0 = __fdividef(1.f, den[0] + 1e-6f), r1 = __fdividef(1.f, den[1] + 1e-6f);
            p[2 * jj] = pack_bf16(num[0] * r0, num[1] * r1);
            p[2 * jj + 1] = pack_bf16(num[2] * r0, num[3] * r1);
          }
        }
        const uint32_t a = act0 + j * SLOT_BYTES + w * HALF_BYTES + loff;
        stage_frag(a, tail_ok ? a + 8 * 1024 : sb + OFF_DUMMY, p);
        mbar_arrive_pred(sb + BAR_PUB + 8 * (t - 1), 1, lane == 0);
      }
    }
  }
}

__device__ __nv_bfloat16 fb_a[S_TOK * DM], fb_qkv[S_TOK * 3 * DM], fb_o[S_TOK * DM], fb_h[S_TOK * DM], fb_g[S_TOK * FF], fb_u[S_TOK * FF];
__device__ float fb_kv[32 * 272];

__global__ void fb_ln(const __nv_bfloat16* __restrict__ x, __nv_bfloat16* __restrict__ y) {
  const int row = blockIdx.x * 8 + (threadIdx.x >> 5), lane = threadIdx.x & 31;
  float v[16], s = 0.f, ss = 0.f;
  for (int i = 0; i < 16; i++) { v[i] = __bfloat162float(x[(size_t)row * DM + lane + 32 * i]); s += v[i]; }
  for (int o = 16; o > 0; o >>= 1) s += __shfl_xor_sync(0xffffffffu, s, o);
  s *= 1.f / DM;
  for (int i = 0; i < 16; i++) ss += (v[i] - s) * (v[i] - s);
  for (int o = 16; o > 0; o >>= 1) ss += __shfl_xor_sync(0xffffffffu, ss, o);
  const float rs = rsqrtf(ss * (1.f / DM) + 1e-5f);
  for (int i = 0; i < 16; i++) y[(size_t)row * DM + lane + 32 * i] = __float2bfloat16((v[i] - s) * rs);
}
__global__ void fb_gemm(const __nv_bfloat16* __restrict__ A, const __nv_bfloat16* __restrict__ B, __nv_bfloat16* C,
                        const __nv_bfloat16* res, const __nv_bfloat16* mul, int N, int K) {
  __shared__ float sa[16][17], sbm[16][17];
  const int tx = threadIdx.x & 15, ty = threadIdx.x >> 4, row = blockIdx.y * 16 + ty, col = blockIdx.x * 16 + tx;
  float acc = 0.f;
  for (int k0 = 0; k0 < K; k0 += 16) {
    sa[ty][tx] = __bfloat162float(A[(size_t)row * K + k0 + tx]);
    sbm[ty][tx] = __bfloat162float(B[(size_t)(k0 + ty) * N + col]);
    __syncthreads();
    for (int k = 0; k < 16; k++) acc = fmaf(sa[ty][k], sbm[k][tx], acc);
    __syncthreads();
  }
  acc = __bfloat162float(__float2bfloat16(acc));
  if (mul) acc *= __bfloat162float(mul[(size_t)row * N + col]);
  if (res) acc += __bfloat162float(res[(size_t)row * N + col]);
  C[(size_t)row * N + col] = __float2bfloat16(acc);
}
__device__ __forceinline__ float fb_phi(__nv_bfloat16 b) {
  const float t = __bfloat162float(b);
  return __bfloat162float(__float2bfloat16((t > 0.f ? t + 1.f : expf(t)) + 1e-6f));
}
__global__ void fb_kvsum(const __nv_bfloat16* __restrict__ qkv, float* __restrict__ kv) {
  const int h = blockIdx.x, d = threadIdx.x >> 4, e = threadIdx.x & 15;
  float a = 0.f, z = 0.f;
  for (int s = 0; s < S_TOK; s++) {
    const float pk = fb_phi(qkv[(size_t)s * 3 * DM + DM + h * 16 + d]);
    a = fmaf(pk, __bfloat162float(qkv[(size_t)s * 3 * DM + 2 * DM + h * 16 + e]), a);
    z += pk;
  }
  kv[h * 272 + d * 16 + e] = __bfloat162float(__float2bfloat16(a));
  if (e == 0) kv[h * 272 + 256 + d] = __bfloat162float(__float2bfloat16(z));
}
__global__ void fb_attn(const __nv_bfloat16* __restrict__ qkv, const float* __restrict__ kv, __nv_bfloat16* __restrict__ o) {
  const int s = blockIdx.x, c = threadIdx.x, h = c >> 4, e = c & 15;
  float num = 0.f, den = 0.f;
  for (int d = 0; d < 16; d++) {
    const float pq = fb_phi(qkv[(size_t)s * 3 * DM + h * 16 + d]);
    num = fmaf(pq, kv[h * 272 + d * 16 + e], num);
    den = fmaf(pq, kv[h * 272 + 256 + d], den);
  }
  o[(size_t)s * DM + c] = __float2bfloat16(num / (den + 1e-6f));
}

void run_fallback(void* const* d_in, void* d_out) {
  typedef __nv_bfloat16 bf;
  void *a, *qkv, *o, *h, *g, *u, *kv;
  cudaGetSymbolAddress(&a, fb_a); cudaGetSymbolAddress(&qkv, fb_qkv); cudaGetSymbolAddress(&o, fb_o);
  cudaGetSymbolAddress(&h, fb_h); cudaGetSymbolAddress(&g, fb_g); cudaGetSymbolAddress(&u, fb_u); cudaGetSymbolAddress(&kv, fb_kv);
  cudaStream_t st = cudaStreamPerThread;
  const bf* x = (const bf*)d_in[0];
  fb_ln<<<S_TOK / 8, 256, 0, st>>>(x, (bf*)a);
  fb_gemm<<<dim3(3 * DM / 16, S_TOK / 16), 256, 0, st>>>((bf*)a, (const bf*)d_in[1], (bf*)qkv, nullptr, nullptr, 3 * DM, DM);
  fb_kvsum<<<32, 256, 0, st>>>((bf*)qkv, (float*)kv);
  fb_attn<<<S_TOK, DM, 0, st>>>((bf*)qkv, (float*)kv, (bf*)o);
  fb_gemm<<<dim3(DM / 16, S_TOK / 16), 256, 0, st>>>((bf*)o, (const bf*)d_in[2], (bf*)h, x, nullptr, DM, DM);
  fb_ln<<<S_TOK / 8, 256, 0, st>>>((bf*)h, (bf*)a);
  fb_gemm<<<dim3(FF / 16, S_TOK / 16), 256, 0, st>>>((bf*)a, (const bf*)d_in[4], (bf*)g, nullptr, nullptr, FF, DM);
  fb_gemm<<<dim3(FF / 16, S_TOK / 16), 256, 0, st>>>((bf*)a, (const bf*)d_in[5], (bf*)u, nullptr, (bf*)g, FF, DM);
  fb_gemm<<<dim3(DM / 16, S_TOK / 16), 256, 0, st>>>((bf*)u, (const bf*)d_in[6], (bf*)d_out, (bf*)h, nullptr, DM, FF);
}

typedef CUresult (*EncodeFn)(CUtensorMap*, CUtensorMapDataType, cuuint32_t, void*, const cuuint64_t*, const cuuint64_t*,
                             const cuuint32_t*, const cuuint32_t*, CUtensorMapInterleave, CUtensorMapSwizzle,
                             CUtensorMapL2promotion, CUtensorMapFloatOOBfill);

void make_map(EncodeFn enc, CUtensorMap* m, const void* base, int rows, int cols, int box_rows) {
  cuuint64_t dims[2] = {(cuuint64_t)cols, (cuuint64_t)rows};
  cuuint64_t strides[1] = {(cuuint64_t)cols * 2};
  cuuint32_t box[2] = {64, (cuuint32_t)box_rows};
  cuuint32_t es[2] = {1, 1};
  enc(m, CU_TENSOR_MAP_DATA_TYPE_BFLOAT16, 2, const_cast<void*>(base), dims, strides, box, es, CU_TENSOR_MAP_INTERLEAVE_NONE,
      CU_TENSOR_MAP_SWIZZLE_128B, CU_TENSOR_MAP_L2_PROMOTION_L2_128B, CU_TENSOR_MAP_FLOAT_OOB_FILL_NONE);
}

}

extern "C" void kernel_launch(void* const* d_in, const int* in_sizes, int n_in, void* d_out, int out_size) {
  (void)in_sizes; (void)n_in; (void)out_size;
  static EncodeFn enc = nullptr;
  static void* pscr = nullptr;
  static bool fused_ok = false;
  cudaLaunchConfig_t cfg = {};
  cfg.gridDim = dim3(NCL * CL);
  cfg.blockDim = dim3(384);
  cfg.dynamicSmemBytes = SMEM_ALLOC;
  cfg.stream = cudaStreamPerThread;
  cudaLaunchAttribute at[1];
  at[0].id = cudaLaunchAttributeClusterDimension;
  at[0].val.clusterDim.x = CL;
  at[0].val.clusterDim.y = 1;
  at[0].val.clusterDim.z = 1;
  cfg.attrs = at;
  cfg.numAttrs = 1;
  if (!pscr) {
    void* fn = nullptr;
    cudaDriverEntryPointQueryResult qr;
    cudaGetDriverEntryPoint("cuTensorMapEncodeTiled", &fn, cudaEnableDefault, &qr);
    enc = (EncodeFn)fn;
    cudaGetSymbolAddress(&pscr, g_scr);
    cudaFuncSetAttribute(fused_kernel, cudaFuncAttributeMaxDynamicSharedMemorySize, SMEM_ALLOC);
    int nclusters = 0;
    fused_ok = enc && cudaOccupancyMaxActiveClusters(&nclusters, fused_kernel, &cfg) == cudaSuccess && nclusters >= NCL;
    (void)cudaGetLastError();
  }
  if (!fused_ok) {
    run_fallback(d_in, d_out);
    return;
  }
  Params P;
  make_map(enc, &P.x, d_in[0], S_TOK, DM, TH);
  make_map(enc, &P.wqkv, d_in[1], DM, 3 * DM, 64);
  make_map(enc, &P.wo, d_in[2], DM, DM, 64);
  make_map(enc, &P.wg, d_in[4], DM, FF, 64);
  make_map(enc, &P.wu, d_in[5], DM, FF, 64);
  make_map(enc, &P.wd, d_in[6], FF, DM, 64);
  make_map(enc, &P.scr, pscr, NCL * SCR_TILES * TOKC, 64, TH);
  make_map(enc, &P.out, d_out, S_TOK, DM, TH);
  P.p_x = (const __nv_bfloat16*)d_in[0];
  P.p_wqkv = (const __nv_bfloat16*)d_in[1];
  P.p_wo = (const __nv_bfloat16*)d_in[2];
  P.p_wg = (const __nv_bfloat16*)d_in[4];
  P.p_wu = (const __nv_bfloat16*)d_in[5];
  P.p_wd = (const __nv_bfloat16*)d_in[6];
  P.p_scr = (__nv_bfloat16*)pscr;

  cudaLaunchKernelEx(&cfg, fused_kernel, P);
}
```

```cpp
#include <cuda_runtime.h>
#include <cuda_bf16.h>
#include <cuda.h>
#include <stdint.h>

namespace {

constexpr int S_TOK = 2048, DM = 512, FF = 1376;
constexpr int CL = 8, NCL = 15;
constexpr int TH = 69;
constexpr int TOKC = 2 * TH;
constexpr int SLOT_BYTES = 144 * 128;
constexpr int HALF_BYTES = 72 * 128;
constexpr int BOX_BYTES = TH * 128;
constexpr int TILE_TX = 2 * BOX_BYTES;
constexpr int WST = 5;
constexpr int WST_BYTES = 128 * 128;
constexpr int STAGGER = 180;
constexpr int NFT = 22;

constexpr int OFF_ACT = 0;
constexpr int OFF_RING = 8 * SLOT_BYTES;
constexpr int OFF_STAT = OFF_RING + WST * WST_BYTES;
constexpr int OFF_BAR = OFF_STAT + 144 * 8;
constexpr int BAR_WFULL = OFF_BAR;
constexpr int BAR_WEMPTY = BAR_WFULL + WST * 8;
constexpr int BAR_AFULL = BAR_WEMPTY + WST * 8;
constexpr int BAR_AEMPTY = BAR_AFULL + 64;
constexpr int BAR_STAT = BAR_AEMPTY + 8;
constexpr int BAR_KVDONE = BAR_STAT + 8;
constexpr int BAR_KVRDY = BAR_KVDONE + 8;
constexpr int BAR_PUB = BAR_KVRDY + 8;
constexpr int BAR_VIS = BAR_PUB + 6 * 8;
constexpr int NBAR = 2 * WST + 8 + 4 + 6 + 5;
constexpr int OFF_EPOCH = BAR_VIS + 5 * 8;
constexpr int OFF_DUMMY = (OFF_EPOCH + 4 + 15) & ~15;
constexpr int SMEM_ALLOC = OFF_DUMMY + 16;
static_assert(SMEM_ALLOC <= 232448, "shared memory budget");

struct alignas(64) Params {
  CUtensorMap x, wqkv, wo, wg, wu, wd, scr, out;
  const __nv_bfloat16 *p_x, *p_wqkv, *p_wo, *p_wg, *p_wu, *p_wd;
  __nv_bfloat16* p_scr;
};

constexpr int SCR_TILES = 16 + NFT;
__device__ __align__(1024) __nv_bfloat16 g_scr[NCL * SCR_TILES * TOKC * 64];
__device__ __align__(128) float g_kv[2][32 * 272];
__device__ __align__(128) unsigned g_flag[8 * 32];
__device__ unsigned g_epoch;

__device__ __forceinline__ uint32_t smem_u32(const void* p) { return (uint32_t)__cvta_generic_to_shared(p); }
__device__ __forceinline__ void mbar_init(uint32_t bar, uint32_t cnt) {
  asm volatile("mbarrier.init.shared::cta.b64 [%0], %1;" ::"r"(bar), "r"(cnt) : "memory");
}
__device__ __forceinline__ void mbar_expect_tx(uint32_t bar, uint32_t bytes) {
  asm volatile("mbarrier.arrive.expect_tx.shared::cta.b64 _, [%0], %1;" ::"r"(bar), "r"(bytes) : "memory");
}
__device__ __forceinline__ void mbar_arrive(uint32_t bar) {
  asm volatile("mbarrier.arrive.shared::cta.b64 _, [%0];" ::"r"(bar) : "memory");
}
__device__ __forceinline__ uint32_t mapa(uint32_t addr, uint32_t cta) {
  uint32_t r;
  asm volatile("mapa.shared::cluster.u32 %0, %1, %2;" : "=r"(r) : "r"(addr), "r"(cta));
  return r;
}
constexpr int SPIN_LIMIT = 1 << 18;
__device__ __forceinline__ void mbar_wait(uint32_t bar, uint32_t parity) {
  uint32_t done;
  int it = 0;
  do {
    asm volatile(
        "{ .reg .pred p; mbarrier.try_wait.parity.shared::cta.b64 p, [%1], %2; selp.u32 %0, 1, 0, p; }"
        : "=r"(done) : "r"(bar), "r"(parity) : "memory");
  } while (!done && ++it < SPIN_LIMIT);
}
__device__ __forceinline__ void mbar_wait2(uint32_t bar0, uint32_t par0, uint32_t bar1, uint32_t par1) {
  uint32_t done;
  int it = 0;
  do {
    asm volatile(
        "{ .reg .pred p, q;\n"
        "mbarrier.try_wait.parity.shared::cta.b64 p, [%1], %2;\n"
        "mbarrier.try_wait.parity.shared::cta.b64 q, [%3], %4;\n"
        "and.pred p, p, q;\n"
        "selp.u32 %0, 1, 0, p; }"
        : "=r"(done) : "r"(bar0), "r"(par0), "r"(bar1), "r"(par1) : "memory");
  } while (!done && ++it < SPIN_LIMIT);
}
__device__ __forceinline__ uint32_t mbar_peek3(uint32_t w0, uint32_t pw0, uint32_t a0, uint32_t a1, uint32_t pa) {
  uint32_t done;
  asm volatile(
      "{ .reg .pred p, r, s;\n"
      "mbarrier.test_wait.parity.shared::cta.b64 p, [%1], %2;\n"
      "mbarrier.test_wait.parity.shared::cta.b64 r, [%3], %5;\n"
      "mbarrier.test_wait.parity.shared::cta.b64 s, [%4], %5;\n"
      "and.pred r, r, s;\n"
      "and.pred p, p, r;\n"
      "selp.u32 %0, 1, 0, p; }"
      : "=r"(done) : "r"(w0), "r"(pw0), "r"(a0), "r"(a1), "r"(pa) : "memory");
  return done;
}
__device__ __forceinline__ void mbar_arrive_pred(uint32_t bar, uint32_t cnt, bool pred) {
  asm volatile("{ .reg .pred p; setp.ne.b32 p, %2, 0; @p mbarrier.arrive.shared::cta.b64 _, [%0], %1; }" ::"r"(bar), "r"(cnt), "r"((int)pred) : "memory");
}
__device__ __forceinline__ void mbar_expect_tx_pred(uint32_t bar, uint32_t bytes, bool pred) {
  asm volatile("{ .reg .pred p; setp.ne.b32 p, %2, 0; @p mbarrier.arrive.expect_tx.shared::cta.b64 _, [%0], %1; }" ::"r"(bar), "r"(bytes), "r"((int)pred) : "memory");
}
__device__ __forceinline__ void mbar_arrive_remote_pred(uint32_t bar, uint32_t cta, uint32_t cnt, bool pred) {
  asm volatile("{ .reg .pred p; .reg .b32 ra; setp.ne.b32 p, %2, 0; mapa.shared::cluster.u32 ra, %0, %1; @p mbarrier.arrive.shared::cluster.b64 _, [ra], %3; }" ::"r"(bar), "r"(cta), "r"((int)pred), "r"(cnt) : "memory");
}
__device__ __forceinline__ void st_async_v2(uint32_t raddr, float a, float b, uint32_t rbar) {
  asm volatile("st.async.weak.shared::cluster.mbarrier::complete_tx::bytes.v2.f32 [%0], {%1, %2}, [%3];" ::"r"(raddr), "f"(a), "f"(b),
               "r"(rbar) : "memory");
}
__device__ __forceinline__ float2 ld_relaxed_v2(const float* p) {
  float2 v;
  asm volatile("ld.relaxed.gpu.global.v2.f32 {%0, %1}, [%2];" : "=f"(v.x), "=f"(v.y) : "l"(p) : "memory");
  return v;
}
__device__ __forceinline__ void st_global_v2_pred(void* p, uint32_t a, uint32_t b, bool pred) {
  asm volatile("{ .reg .pred p; setp.ne.b32 p, %3, 0; @p st.global.v2.b32 [%0], {%1, %2}; }" ::"l"(p), "r"(a), "r"(b), "r"((int)pred) : "memory");
}
__device__ __forceinline__ void tma_load(uint32_t dst, const CUtensorMap* m, int c0, int c1, uint32_t bar) {
  asm volatile(
      "cp.async.bulk.tensor.2d.shared::cluster.global.mbarrier::complete_tx::bytes [%0], [%1, {%3, %4}], [%2];" ::"r"(dst),
      "l"(m), "r"(bar), "r"(c0), "r"(c1) : "memory");
}
__device__ __forceinline__ void tma_load_mc(uint32_t dst, const CUtensorMap* m, int c0, int c1, uint32_t bar) {
  asm volatile(
      "cp.async.bulk.tensor.2d.shared::cluster.global.mbarrier::complete_tx::bytes.multicast::cluster [%0], [%1, {%3, "
      "%4}], [%2], %5;" ::"r"(dst),
      "l"(m), "r"(bar), "r"(c0), "r"(c1), "h"((uint16_t)0xFF) : "memory");
}
__device__ __forceinline__ void tma_store(const CUtensorMap* m, int c0, int c1, uint32_t src) {
  asm volatile("cp.async.bulk.tensor.2d.global.shared::cta.bulk_group [%0, {%2, %3}], [%1];" ::"l"(m), "r"(src), "r"(c0),
               "r"(c1) : "memory");
}
__device__ __forceinline__ void bulk_commit() { asm volatile("cp.async.bulk.commit_group;" ::: "memory"); }
__device__ __forceinline__ void bulk_wait_all() { asm volatile("cp.async.bulk.wait_group 0;" ::: "memory"); }
__device__ __forceinline__ void bulk_wait_read() { asm volatile("cp.async.bulk.wait_group.read 0;" ::: "memory"); }
__device__ __forceinline__ void fence_async_smem() { asm volatile("fence.proxy.async.shared::cta;" ::: "memory"); }
__device__ __forceinline__ void prefetch_tmap(const CUtensorMap* m) {
  asm volatile("prefetch.tensormap [%0];" ::"l"(m) : "memory");
}
__device__ __forceinline__ void l2_prefetch(const void* p, uint32_t bytes) {
  asm volatile("cp.async.bulk.prefetch.L2.global [%0], %1;" ::"l"(p), "r"(bytes) : "memory");
}
#define WG_FENCE() asm volatile("wgmma.fence.sync.aligned;" ::: "memory")
#define WG_COMMIT() asm volatile("wgmma.commit_group.sync.aligned;" ::: "memory")
#define WG_WAIT(n) asm volatile("wgmma.wait_group.sync.aligned %0;" ::"n"(n) : "memory")
template <int N>
__device__ __forceinline__ void fence_acc(float (&d)[N]) {
#pragma unroll
  for (int i = 0; i < N; i++) asm volatile("" : "+f"(d[i])::"memory");
}
constexpr uint32_t DESC_HI = 0x40000000u | (1024 >> 4);
__device__ __forceinline__ uint32_t mk_desc(uint32_t addr) { return ((addr & 0x3FFFF) >> 4) | (1u << 16); }

__device__ __forceinline__ void wgmma_n72(float (&d)[36], uint32_t da, uint32_t db, int scale_d) {
  asm volatile("{ .reg .pred p; .reg .b64 da, db; setp.ne.b32 p, %38, 0;\n"
    "mov.b64 da, {%36, %39}; mov.b64 db, {%37, %39};\n"
    "wgmma.mma_async.sync.aligned.m64n72k16.f32.bf16.bf16 {"
    "%0,%1,%2,%3,%4,%5,%6,%7,%8,%9,%10,%11,"
    "%12,%13,%14,%15,%16,%17,%18,%19,%20,%21,%22,%23,"
    "%24,%25,%26,%27,%28,%29,%30,%31,%32,%33,%34,%35"
    "}, da, db, p, 1, 1, 1, 0; }"
    : "+f"(d[0]), "+f"(d[1]), "+f"(d[2]), "+f"(d[3]), "+f"(d[4]), "+f"(d[5]), "+f"(d[6]), "+f"(d[7]),
      "+f"(d[8]), "+f"(d[9]), "+f"(d[10]), "+f"(d[11]), "+f"(d[12]), "+f"(d[13]), "+f"(d[14]), "+f"(d[15]),
      "+f"(d[16]), "+f"(d[17]), "+f"(d[18]), "+f"(d[19]), "+f"(d[20]), "+f"(d[21]), "+f"(d[22]), "+f"(d[23]),
      "+f"(d[24]), "+f"(d[25]), "+f"(d[26]), "+f"(d[27]), "+f"(d[28]), "+f"(d[29]), "+f"(d[30]), "+f"(d[31]),
      "+f"(d[32]), "+f"(d[33]), "+f"(d[34]), "+f"(d[35])
    : "r"(da), "r"(db), "r"(scale_d), "r"(DESC_HI));
}

__device__ __forceinline__ void wgmma_n144(float (&d)[72], uint32_t da, uint32_t db, int scale_d) {
  asm volatile("{ .reg .pred p; .reg .b64 da, db; setp.ne.b32 p, %74, 0;\n"
    "mov.b64 da, {%72, %75}; mov.b64 db, {%73, %75};\n"
    "wgmma.mma_async.sync.aligned.m64n144k16.f32.bf16.bf16 {"
    "%0,%1,%2,%3,%4,%5,%6,%7,%8,%9,%10,%11,"
    "%12,%13,%14,%15,%16,%17,%18,%19,%20,%21,%22,%23,"
    "%24,%25,%26,%27,%28,%29,%30,%31,%32,%33,%34,%35,"
    "%36,%37,%38,%39,%40,%41,%42,%43,%44,%45,%46,%47,"
    "%48,%49,%50,%51,%52,%53,%54,%55,%56,%57,%58,%59,"
    "%60,%61,%62,%63,%64,%65,%66,%67,%68,%69,%70,%71"
    "}, da, db, p, 1, 1, 1, 0; }"
    : "+f"(d[0]), "+f"(d[1]), "+f"(d[2]), "+f"(d[3]), "+f"(d[4]), "+f"(d[5]), "+f"(d[6]), "+f"(d[7]),
      "+f"(d[8]), "+f"(d[9]), "+f"(d[10]), "+f"(d[11]), "+f"(d[12]), "+f"(d[13]), "+f"(d[14]), "+f"(d[15]),
      "+f"(d[16]), "+f"(d[17]), "+f"(d[18]), "+f"(d[19]), "+f"(d[20]), "+f"(d[21]), "+f"(d[22]), "+f"(d[23]),
      "+f"(d[24]), "+f"(d[25]), "+f"(d[26]), "+f"(d[27]), "+f"(d[28]), "+f"(d[29]), "+f"(d[30]), "+f"(d[31]),
      "+f"(d[32]), "+f"(d[33]), "+f"(d[34]), "+f"(d[35]), "+f"(d[36]), "+f"(d[37]), "+f"(d[38]), "+f"(d[39]),
      "+f"(d[40]), "+f"(d[41]), "+f"(d[42]), "+f"(d[43]), "+f"(d[44]), "+f"(d[45]), "+f"(d[46]), "+f"(d[47]),
      "+f"(d[48]), "+f"(d[49]), "+f"(d[50]), "+f"(d[51]), "+f"(d[52]), "+f"(d[53]), "+f"(d[54]), "+f"(d[55]),
      "+f"(d[56]), "+f"(d[57]), "+f"(d[58]), "+f"(d[59]), "+f"(d[60]), "+f"(d[61]), "+f"(d[62]), "+f"(d[63]),
      "+f"(d[64]), "+f"(d[65]), "+f"(d[66]), "+f"(d[67]), "+f"(d[68]), "+f"(d[69]), "+f"(d[70]), "+f"(d[71])
    : "r"(da), "r"(db), "r"(scale_d), "r"(DESC_HI));
}


__device__ __forceinline__ void mma16816(float (&c)[4], uint32_t a0, uint32_t a1, uint32_t a2, uint32_t a3, uint32_t b0,
                                         uint32_t b1) {
  asm volatile(
      "mma.sync.aligned.m16n8k16.row.col.f32.bf16.bf16.f32 {%0,%1,%2,%3}, {%4,%5,%6,%7}, {%8,%9}, {%0,%1,%2,%3};"
      : "+f"(c[0]), "+f"(c[1]), "+f"(c[2]), "+f"(c[3])
      : "r"(a0), "r"(a1), "r"(a2), "r"(a3), "r"(b0), "r"(b1));
}
__device__ __forceinline__ uint32_t movmat(uint32_t a) {
  uint32_t d;
  asm volatile("movmatrix.sync.aligned.m8n8.trans.b16 %0, %1;" : "=r"(d) : "r"(a));
  return d;
}
__device__ __forceinline__ void stsm4t(uint32_t addr, uint32_t r0, uint32_t r1, uint32_t r2, uint32_t r3) {
  asm volatile("stmatrix.sync.aligned.m8n8.x4.trans.shared.b16 [%0], {%1,%2,%3,%4};" ::"r"(addr), "r"(r0), "r"(r1),
               "r"(r2), "r"(r3) : "memory");
}
__device__ __forceinline__ void stsm2t(uint32_t addr, uint32_t r0, uint32_t r1) {
  asm volatile("stmatrix.sync.aligned.m8n8.x2.trans.shared.b16 [%0], {%1,%2};" ::"r"(addr), "r"(r0), "r"(r1) : "memory");
}
__device__ __forceinline__ void ldsm4t(uint32_t addr, uint32_t& r0, uint32_t& r1, uint32_t& r2, uint32_t& r3) {
  asm volatile("ldmatrix.sync.aligned.m8n8.x4.trans.shared.b16 {%0,%1,%2,%3}, [%4];"
               : "=r"(r0), "=r"(r1), "=r"(r2), "=r"(r3) : "r"(addr) : "memory");
}
__device__ __forceinline__ void ldsm2t(uint32_t addr, uint32_t& r0, uint32_t& r1) {
  asm volatile("ldmatrix.sync.aligned.m8n8.x2.trans.shared.b16 {%0,%1}, [%2];" : "=r"(r0), "=r"(r1) : "r"(addr) : "memory");
}
__device__ __forceinline__ float4 lds128f(uint32_t addr) {
  float4 v;
  asm volatile("ld.shared.v4.f32 {%0,%1,%2,%3}, [%4];" : "=f"(v.x), "=f"(v.y), "=f"(v.z), "=f"(v.w) : "r"(addr) : "memory");
  return v;
}
__device__ __forceinline__ uint4 lds128u(uint32_t addr) {
  uint4 v;
  asm volatile("ld.shared.v4.u32 {%0,%1,%2,%3}, [%4];" : "=r"(v.x), "=r"(v.y), "=r"(v.z), "=r"(v.w) : "r"(addr) : "memory");
  return v;
}
__device__ __forceinline__ uint32_t pack_bf16(float lo, float hi) {
  uint32_t r;
  asm("cvt.rn.bf16x2.f32 %0, %1, %2;" : "=r"(r) : "f"(hi), "f"(lo));
  return r;
}
__device__ __forceinline__ float bf_lo(uint32_t p) { return __uint_as_float(p << 16); }
__device__ __forceinline__ float bf_hi(uint32_t p) { return __uint_as_float(p & 0xFFFF0000u); }
__device__ __forceinline__ float ex2(float t) {
  float r;
  asm("ex2.approx.ftz.f32 %0, %1;" : "=f"(r) : "f"(t));
  return r;
}
__device__ __forceinline__ void red_add_v2(float* p, float a, float b) {
  asm volatile("red.relaxed.gpu.global.add.v2.f32 [%0], {%1, %2};" ::"l"(p), "f"(a), "f"(b) : "memory");
}

template <int N>
__device__ __forceinline__ void wgmma(float (&d)[N / 2], uint32_t da, uint32_t db, int scale_d) {
  if constexpr (N == 144) wgmma_n144(d, da, db, scale_d);
  else wgmma_n72(d, da, db, scale_d);
}

struct Ring {
  int ws, ph;
  __device__ __forceinline__ void advance() { if (++ws == WST) { ws = 0; ph ^= 1; } }
};

template <int N, bool SAME>
__device__ __forceinline__ void mma_loop(float (&accA)[N / 2], float (&accB)[N / 2], Ring& R, uint32_t sb, uint32_t actB, int n,
                                         int par0, int parmask, uint32_t relcnt, int relsteps, int keepslot, bool arm, int t128, int sigbar) {
  const uint32_t wlo = mk_desc(sb + OFF_RING), alo = mk_desc(actB);
  const bool lead = t128 == 0, lead2 = t128 < (SAME ? 2 : 1);
  const uint32_t l = SAME ? (t128 & 1) : 0;
  auto release = [&](int i, int stage) {
    mbar_arrive_pred(sb + BAR_WEMPTY + 8 * stage, relcnt, lead);
    const uint32_t sl = (SAME ? ((2 * i) & 7) : i) + l;
    const bool mine = (i < relsteps) && lead2 && (int)sl != keepslot;
    mbar_expect_tx_pred(sb + BAR_AFULL + 8 * sl, TILE_TX, mine && arm);
    mbar_arrive_remote_pred(sb + BAR_AEMPTY, sl, (N == 144 && SAME) ? 2 : 1, mine);
  };
  uint32_t tok = 0;
  int prev = 0;
#pragma unroll 1
  for (int i = 0; i < n; i++) {
    const int ws = R.ws;
    const int a = SAME ? ((2 * i) & 7) : i;
    if (!tok) {
      const int pa = (par0 + ((i >> 2) & parmask)) & 1;
      mbar_wait(sb + BAR_WFULL + 8 * ws, R.ph);
      mbar_wait2(sb + BAR_AFULL + 8 * a, pa, sb + BAR_AFULL + 8 * a + (SAME ? 8 : 0), pa);
    }
    R.advance();
    const uint32_t da = wlo + ws * (WST_BYTES >> 4), db = alo + a * (SLOT_BYTES >> 4);
    WG_FENCE();
#pragma unroll
    for (int kk = 0; kk < 3; kk++) wgmma<N>(accA, da + kk * 128, db + kk * 2, 1);
    WG_COMMIT();
    const int i1 = i + 1, a1 = SAME ? ((2 * i1) & 7) : (i1 & 7);
    tok = mbar_peek3(sb + BAR_WFULL + 8 * R.ws, R.ph, sb + BAR_AFULL + 8 * a1, sb + BAR_AFULL + 8 * a1 + (SAME ? 8 : 0),
                     (par0 + ((i1 >> 2) & parmask)) & 1);
    if (sigbar && i == n - 1) asm volatile("bar.arrive %0, 256;" ::"r"(sigbar) : "memory");
    WG_WAIT(1);
    if (i > 0) release(i - 1, prev);
    prev = ws;
    wgmma<N>(accA, da + 384, db + 6, 1);
    if constexpr (SAME) {
#pragma unroll
      for (int kk = 0; kk < 4; kk++) wgmma<N>(accA, da + 512 + kk * 128, db + (SLOT_BYTES >> 4) + kk * 2, 1);
    } else {
#pragma unroll
      for (int kk = 0; kk < 4; kk++) wgmma<N>(accB, da + 512 + kk * 128, db + kk * 2, 1);
    }
    WG_COMMIT();
  }
  WG_WAIT(0);
  fence_acc(accA);
  if constexpr (!SAME) fence_acc(accB);
  release(n - 1, prev);
}

__device__ __forceinline__ void stage_frag(uint32_t a, uint32_t a8, const uint32_t (&p)[18]) {
#pragma unroll
  for (int jj = 0; jj < 8; jj += 2) stsm4t(a + jj * 1024, p[2 * jj], p[2 * jj + 1], p[2 * jj + 2], p[2 * jj + 3]);
  stsm2t(a8, p[16], p[17]);
  fence_async_smem();
  __syncwarp();
}
__device__ __forceinline__ void load_frag(uint32_t a, uint32_t (&p)[18]) {
#pragma unroll
  for (int jj = 0; jj < 8; jj += 2) ldsm4t(a + jj * 1024, p[2 * jj], p[2 * jj + 1], p[2 * jj + 2], p[2 * jj + 3]);
  ldsm2t(a + 8 * 1024, p[16], p[17]);
}
__device__ __forceinline__ void store_frag(char* d, const uint32_t (&p)[18], int q) {
#pragma unroll
  for (int jj = 0; jj < 9; jj++) {
    const uint32_t lo = movmat(p[2 * jj]), hi = movmat(p[2 * jj + 1]);
    const uint32_t recv = __shfl_xor_sync(0xffffffffu, (q & 1) ? lo : hi, 1);
    st_global_v2_pred(d + jj * 1024, (q & 1) ? recv : lo, (q & 1) ? hi : recv, jj < 8 || (threadIdx.x & 31) < 4 * (TH - 64));
  }
}

__global__ void __launch_bounds__(384, 1) fused_kernel(const __grid_constant__ Params P) {
  extern __shared__ __align__(1024) uint8_t smem_raw[];
  const uint32_t sb = smem_u32(smem_raw);
  const int tid = threadIdx.x, warp = __shfl_sync(0xffffffffu, tid >> 5, 0), lane = tid & 31;
  uint32_t rank;
  asm volatile("mov.u32 %0, %%cluster_ctarank;" : "=r"(rank));
  const int j = (int)rank;
  const int cl = blockIdx.x / CL;
  const int tok0 = cl * TOKC;
  const int nr = (j + 16 < NFT) ? 3 : 2;

  if (lane == 0) {
#pragma unroll 1
    for (int b = warp; b < NBAR; b += 12) {
      uint32_t cnt = 1;
      if (b >= WST && b < 2 * WST) cnt = 2;
      const int o = b - (2 * WST + 8);
      if (o == 0) cnt = 16;
      if (o == 2 || (o >= 4 && o < 10)) cnt = 8;
      mbar_init(sb + OFF_BAR + 8 * b, cnt);
    }
    asm volatile("fence.mbarrier_init.release.cluster;" ::: "memory");
  }
  __syncwarp();
  if (warp >= 8) {
    const int i = (tid - 256) * NCL + cl;
    if (i < 3 * DM) {
      const int part = i < 2 * DM ? 1 + (i & 1) : 0, row = i < 2 * DM ? (i >> 1) : i - 2 * DM;
      const char* wp = reinterpret_cast<const char*>(P.p_wqkv) + (size_t)row * (3 * DM * 2) + (512 * part + 64 * j) * 2;
      asm volatile("prefetch.global.L2 [%0];" ::"l"(wp) : "memory");
    }
    if (warp == 9 && lane < 8) prefetch_tmap(&P.x + lane);
  }
  uint4 v[5][2];
  if (warp >= 4 && warp < 8) {
#pragma unroll
    for (int i = 0; i < 5; i++) {
      const int row = 18 * j + min((warp & 3) + 4 * i, 17);
      const int tk = min(tok0 + row - (row >= 72 ? 3 : 0), S_TOK - 1);
      const uint4* src = reinterpret_cast<const uint4*>(P.p_x + (size_t)tk * DM) + lane;
      v[i][0] = __ldg(src);
      v[i][1] = __ldg(src + 32);
    }
  }
  if (warp < 4 && lane < 24) {
#pragma unroll
    for (int k = 0; k < 4; k++)
      asm volatile("st.shared.v4.u32 [%0], {%1,%1,%1,%1};" ::"r"(sb + OFF_ACT + (warp + 4 * k) * HALF_BYTES + 69 * 128 + lane * 16),
                   "r"(lane >= 16 ? 0x3F803F80u : 0u) : "memory");
    fence_async_smem();
  }
  __syncthreads();
  asm volatile("barrier.cluster.arrive.relaxed.aligned;" ::: "memory");

  if (warp >= 8) {
    if (lane == 0) {
      if (warp == 8) {
        mbar_expect_tx(sb + BAR_STAT, 144 * 8);
      } else if (warp == 9) {
#pragma unroll 1
        for (int n = 0; n < 3; n++) {
          const uint32_t dst = sb + OFF_RING + n * WST_BYTES, bar = sb + BAR_WFULL + 8 * n;
          mbar_expect_tx(bar, WST_BYTES);
          tma_load(dst, &P.wqkv, 64 * j + 512, 64 * n, bar);
          tma_load(dst + WST_BYTES / 2, &P.wqkv, 64 * j + 1024, 64 * n, bar);
        }
      } else if (warp > 9) {
#pragma unroll 1
        for (int s = warp - 10; s < 8; s += 2) {
          mbar_expect_tx(sb + BAR_AFULL + 8 * s, TILE_TX);
          tma_load(sb + OFF_ACT + s * SLOT_BYTES, &P.x, 64 * s, tok0, sb + BAR_AFULL + 8 * s);
          tma_load(sb + OFF_ACT + s * SLOT_BYTES + HALF_BYTES, &P.x, 64 * s, tok0 + TH, sb + BAR_AFULL + 8 * s);
        }
      }
    }
    __syncwarp();
    asm volatile("setmaxnreg.dec.sync.aligned.u32 40;");
    if (warp == 8) {
      if (lane == 0) {
        const int nstage = 16 + 8 * nr + NFT / 2;
        int st = 3, ph = 1;
#pragma unroll 1
        for (int n = 3; n < nstage; n++) {
          const uint32_t dst = sb + OFF_RING + st * WST_BYTES, bar = sb + BAR_WFULL + 8 * st;
          if (n >= WST) mbar_wait(sb + BAR_WEMPTY + 8 * st, ph);
          if (++st == WST) { st = 0; ph ^= 1; }
          mbar_expect_tx(bar, WST_BYTES);
          const CUtensorMap *m0, *m1;
          int c0 = 64 * j, c1 = c0, r0, r1;
          if (n < 8) { m0 = m1 = &P.wqkv; c0 += 512; c1 += 1024; r0 = r1 = 64 * n; }
          else if (n < 16) { m0 = m1 = n < 12 ? &P.wqkv : &P.wo; r0 = 128 * (n & 3); r1 = r0 + 64; }
          else if (n < 16 + 8 * nr) { m0 = &P.wg; m1 = &P.wu; c0 += 512 * ((n - 16) >> 3); c1 = c0; r0 = r1 = 64 * (n & 7); }
          else { m0 = m1 = &P.wd; r0 = 128 * (n - 16 - 8 * nr); r1 = r0 + 64; }
          tma_load(dst, m0, c0, r0, bar);
          tma_load(dst + WST_BYTES / 2, m1, c1, r1, bar);
        }
      }
    } else if (warp == 9) {
      asm volatile("barrier.cluster.wait.acquire.aligned;" ::: "memory");
      if (lane == 0) {
        const uint32_t slot = sb + OFF_ACT + j * SLOT_BYTES, af = sb + BAR_AFULL + 8 * j;
#pragma unroll 1
        for (int e = 1; e < 3 + nr; e++) {
          const int row = (cl * SCR_TILES + 8 * (e - 1) + j) * TOKC;
          mbar_wait(sb + BAR_VIS + 8 * (e - 1), 0);
          asm volatile("fence.proxy.async.global;" ::: "memory");
          mbar_wait(sb + BAR_AEMPTY, (e - 1) & 1);
          if (e < 3) {
            const long long t0 = clock64();
            while (clock64() - t0 < (long long)j * STAGGER) {}
          }
          tma_load_mc(slot, &P.scr, 0, row, af);
          tma_load_mc(slot + HALF_BYTES, &P.scr, 0, row + TH, af);
        }
      }
    } else if (warp == 10) {
      unsigned epoch = 0;
      if (lane == 0) asm volatile("ld.relaxed.gpu.global.u32 %0, [%1];" : "=r"(epoch) : "l"(&g_epoch) : "memory");
      epoch = __shfl_sync(0xffffffffu, epoch, 0);
      if (lane == 0) asm volatile("st.shared.u32 [%0], %1;" ::"r"(sb + OFF_EPOCH), "r"(epoch) : "memory");
      __syncwarp();
      asm volatile("bar.arrive 12, 160;" ::: "memory");
      asm volatile("bar.arrive 13, 160;" ::: "memory");
      if (cl == 0) {
        float* z = &g_kv[(epoch + 1) & 1][j * 4 * 272];
#pragma unroll 1
        for (int i = lane; i < 4 * 272; i += 32) z[i] = 0.f;
      }
      mbar_wait(sb + BAR_KVDONE, 0);
      const unsigned target = (epoch + 1u) * NCL;
      if (lane == 0) {
        asm volatile("fence.acq_rel.gpu;" ::: "memory");
        asm volatile("red.relaxed.gpu.global.add.u32 [%0], %1;" ::"l"(&g_flag[j * 32]), "r"(1u) : "memory");
        unsigned v;
        int n = 0;
        do {
          asm volatile("ld.acquire.gpu.global.u32 %0, [%1];" : "=r"(v) : "l"(&g_flag[j * 32]) : "memory");
        } while ((int)(v - target) < 0 && ++n < SPIN_LIMIT);
      }
      __syncwarp();
      if (lane == 0) mbar_arrive(sb + BAR_KVRDY);
      if (blockIdx.x == 0) {
        unsigned v2 = target;
        int n = 0;
        do {
          if (lane < 8) asm volatile("ld.acquire.gpu.global.u32 %0, [%1];" : "=r"(v2) : "l"(&g_flag[lane * 32]) : "memory");
        } while (__any_sync(0xffffffffu, (int)(v2 - target) < 0) && ++n < SPIN_LIMIT);
        if (lane == 0) asm volatile("st.relaxed.gpu.global.u32 [%0], %1;" ::"l"(&g_epoch), "r"(epoch + 1u) : "memory");
      }
    } else {
      mbar_wait(sb + BAR_AFULL + 8 * 7, 0);
      if (lane < 4) {
        const uint32_t total = lane == 0 ? 512u * 512u * 2u : 512u * 1376u * 2u;
        const uint32_t chunk = lane == 0 ? 4480u : 11776u;
        const char* base = (const char*)(lane == 0 ? P.p_wo : lane == 1 ? P.p_wg : lane == 2 ? P.p_wu : P.p_wd);
        const uint32_t off = blockIdx.x * chunk;
        if (off < total) l2_prefetch(base + off, min(chunk, total - off));
      }
      if (lane == 0) {
        const uint32_t slot = sb + OFF_ACT + j * SLOT_BYTES;
#pragma unroll 1
        for (int e = 0; e < 3 + nr; e++) {
          const bool last = (e == 2 + nr);
          mbar_wait(sb + BAR_PUB + 8 * (last ? 5 : e), 0);
          if (e < 2 || last) {
            const CUtensorMap* m = last ? &P.out : &P.scr;
            const int c0 = last ? 64 * j : 0, c1 = last ? tok0 : (cl * SCR_TILES + 8 * e + j) * TOKC;
            tma_store(m, c0, c1, slot);
            tma_store(m, c0, c1 + TH, slot + HALF_BYTES);
            bulk_commit();
            if (last) { bulk_wait_read(); break; }
            bulk_wait_all();
          } else {
            asm volatile("fence.acq_rel.gpu;" ::: "memory");
          }
          mbar_arrive(sb + BAR_VIS + 8 * e);
        }
      }
    }
  } else {
    asm volatile("setmaxnreg.inc.sync.aligned.u32 232;");
    const int w = warp >> 2, w4 = warp & 3;
    const uint32_t act0 = sb + OFF_ACT;
    const int tokw = tok0 + w * TH;
    Ring R = {0, 0};
    uint32_t hres[18];

#pragma unroll 1
    for (int t = 0; t < 4; t++) {
      int lane = tid & 31;
      asm volatile("" : "+r"(lane));
      const int g = lane >> 2, q = lane & 3, t128 = w4 * 32 + lane;
      const int nvalid = min(TH, S_TOK - tokw);
      const uint32_t loff = (uint32_t)((8 * (lane >> 4) + (lane & 7)) * 128 + (((2 * w4 + ((lane >> 3) & 1)) ^ (lane & 7)) << 4));
      const bool tail_ok = (lane & 7) < TH - 64;
      if (w == 1 && (t == 0 || t == 3)) {
        if (t == 3) {
#pragma unroll 1
          for (int s = 0; s < 8; s++) mbar_wait(sb + BAR_AFULL + 8 * s, 0);
#pragma unroll
          for (int i = 0; i < 5; i++) {
            const int row = 18 * j + min(w4 + 4 * i, 17);
            const uint32_t a = act0 + (lane >> 3) * SLOT_BYTES + row * 128 + (((lane & 7) ^ (row & 7)) << 4);
            v[i][0] = lds128u(a);
            v[i][1] = lds128u(a + 4 * SLOT_BYTES);
          }
        }
        float s1[5], s2[5], piv[5];
#pragma unroll
        for (int i = 0; i < 5; i++) {
          piv[i] = __shfl_sync(0xffffffffu, bf_lo(v[i][0].x), 0);
          s1[i] = 0.f; s2[i] = 0.f;
#pragma unroll
          for (int k = 0; k < 2; k++) {
            const uint32_t u[4] = {v[i][k].x, v[i][k].y, v[i][k].z, v[i][k].w};
#pragma unroll
            for (int e = 0; e < 4; e++) {
              const float d0 = bf_lo(u[e]) - piv[i], d1 = bf_hi(u[e]) - piv[i];
              s1[i] += d0 + d1;
              s2[i] = fmaf(d0, d0, fmaf(d1, d1, s2[i]));
            }
          }
        }
#pragma unroll
        for (int o = 1; o < 32; o <<= 1) {
#pragma unroll
          for (int i = 0; i < 5; i++) {
            s1[i] += __shfl_xor_sync(0xffffffffu, s1[i], o);
            s2[i] += __shfl_xor_sync(0xffffffffu, s2[i], o);
          }
        }
        if (t == 0) asm volatile("barrier.cluster.wait.acquire.aligned;" ::: "memory");
        if (lane < CL) {
          const uint32_t rstat = mapa(sb + OFF_STAT, lane), rbar = mapa(sb + BAR_STAT, lane);
#pragma unroll
          for (int i = 0; i < 5; i++) {
            const int row = 18 * j + w4 + 4 * i;
            const int hf = row >= 72, rr = row - 72 * hf;
            const float md = s1[i] * (1.f / DM);
            const float var = fmaxf(s2[i] * (1.f / DM) - md * md, 0.f);
            const bool valid = rr < TH && tok0 + hf * TH + rr < S_TOK;
            if (w4 + 4 * i < 18) st_async_v2(rstat + row * 8, piv[i] + md, valid ? rsqrtf(var + 1e-5f) : 0.f, rbar);
          }
        }
      } else if (t == 0) {
        asm volatile("barrier.cluster.wait.acquire.aligned;" ::: "memory");
      }
#pragma unroll
      for (int i = 0; i < 5; i++) v[i][0] = v[i][1] = make_uint4(0u, 0u, 0u, 0u);
      auto fetch_res = [&]() {
        mbar_wait(sb + BAR_AFULL + 8 * j, 0);
        load_frag(act0 + j * SLOT_BYTES + w * HALF_BYTES + loff, hres);
      };
      if (t == 3) {
        const int wd = nr & 1;
        float accA[72], accB[72];
#pragma unroll 1
        for (int r = 0; r < nr; r++) {
          if ((r & 1) != w) {
            if (r == nr - 1) {
              uint32_t chk = 0;
#pragma unroll
              for (int hf = 0; hf < 2; hf++) {
                uint32_t hr[18];
                load_frag(act0 + j * SLOT_BYTES + hf * HALF_BYTES + loff, hr);
                chk ^= hr[0] ^ hr[4] ^ hr[8] ^ hr[12] ^ hr[16];
#pragma unroll
                for (int i = 0; i < 18; i++) {
                  accB[36 * hf + (i >> 1) * 4 + (i & 1) * 2] = bf_lo(hr[i]);
                  accB[36 * hf + (i >> 1) * 4 + (i & 1) * 2 + 1] = bf_hi(hr[i]);
                }
              }
              asm volatile("st.shared.u32 [%0], %1;" ::"r"(sb + OFF_DUMMY), "r"(chk) : "memory");
              asm volatile("bar.sync %0, 128;" ::"r"(8 + w) : "memory");
              mbar_expect_tx_pred(sb + BAR_AFULL + 8 * j, TILE_TX, t128 == 0 && w == 0);
              mbar_arrive_pred(sb + BAR_AEMPTY, 1, t128 == 0);
            }
            asm volatile("bar.sync %0, 256;" ::"r"(2 + r) : "memory");
#pragma unroll 1
            for (int i = 0; i < 8; i++) R.advance();
            continue;
          }
          const bool lastread = (r + 2 >= nr);
#pragma unroll
          for (int i = 0; i < 72; i++) { accA[i] = 0.f; accB[i] = 0.f; }
          mma_loop<144, false>(accA, accB, R, sb, act0, 8, 0, 0, 2, lastread ? 8 : 0, w == wd ? j : -1, w == 0, t128, 2 + r);
          mbar_wait(sb + BAR_STAT, 1);
#pragma unroll 1
          for (int hf = 0; hf < 2; hf++) {
            const float a0 = __shfl_sync(0xffffffffu, accA[33], lane | 3), a1 = __shfl_sync(0xffffffffu, accA[35], lane | 3);
            const float b0 = __shfl_sync(0xffffffffu, accB[33], lane | 3), b1 = __shfl_sync(0xffffffffu, accB[35], lane | 3);
            uint32_t p[18];
            float4 sts[9];
#pragma unroll
            for (int jj = 0; jj < 9; jj++) sts[jj] = lds128f(sb + OFF_STAT + (72 * hf + 8 * jj + 2 * q) * 8);
#pragma unroll
            for (int jj = 0; jj < 9; jj++) {
              const float4 st = sts[jj];
              const float r0 = st.y * st.y, r1 = st.w * st.w;
              p[2 * jj] = pack_bf16(r0 * (fmaf(-st.x, a0, accA[4 * jj]) * fmaf(-st.x, b0, accB[4 * jj])),
                                    r1 * (fmaf(-st.z, a0, accA[4 * jj + 1]) * fmaf(-st.z, b0, accB[4 * jj + 1])));
              p[2 * jj + 1] = pack_bf16(r0 * (fmaf(-st.x, a1, accA[4 * jj + 2]) * fmaf(-st.x, b1, accB[4 * jj + 2])),
                                        r1 * (fmaf(-st.z, a1, accA[4 * jj + 3]) * fmaf(-st.z, b1, accB[4 * jj + 3])));
            }
            store_frag(reinterpret_cast<char*>(P.p_scr) + (size_t)((cl * SCR_TILES + 16 + 8 * r + j) * TOKC + hf * TH + g) * 128 +
                           (16 * w4 + (q & 1) * 8 + (q >> 1) * 4) * 2, p, q);
#pragma unroll
            for (int i = 0; i < 36; i++) { accA[i] = accA[i + 36]; accB[i] = accB[i + 36]; }
          }
          __syncwarp();
          mbar_arrive_pred(sb + BAR_PUB + 8 * (2 + r), 2, lane == 0);
        }
        if (w == wd) {
          float accD[72];
#pragma unroll
          for (int i = 0; i < 72; i++) accD[i] = accB[i];
          fence_acc(accD);
          mma_loop<144, true>(accD, accD, R, sb, act0, NFT / 2, 3, 3, 2, (NFT - 8) / 2, -1, true, t128, 0);
#pragma unroll
          for (int hf = 0; hf < 2; hf++) {
            uint32_t p[18];
#pragma unroll
            for (int i = 0; i < 18; i++)
              p[i] = pack_bf16(accD[36 * hf + (i >> 1) * 4 + (i & 1) * 2], accD[36 * hf + (i >> 1) * 4 + (i & 1) * 2 + 1]);
            const uint32_t a = act0 + j * SLOT_BYTES + hf * HALF_BYTES + loff;
            stage_frag(a, tail_ok ? a + 8 * 1024 : sb + OFF_DUMMY, p);
          }
          mbar_arrive_pred(sb + BAR_PUB + 8 * 5, 2, lane == 0);
        }
        break;
      }
      if (t == 1) fetch_res();
      float acc[36];
      uint32_t pv[18];
      if (t == 2) {
#pragma unroll
        for (int i = 0; i < 18; i++) {
          acc[(i >> 1) * 4 + (i & 1) * 2] = bf_lo(hres[i]);
          acc[(i >> 1) * 4 + (i & 1) * 2 + 1] = bf_hi(hres[i]);
        }
      } else {
#pragma unroll
        for (int i = 0; i < 36; i++) acc[i] = 0.f;
      }
      auto load_stats = [&](float4 (&st)[9]) {
#pragma unroll
        for (int jj = 0; jj < 9; jj++) st[jj] = lds128f(sb + OFF_STAT + (72 * w + 8 * jj + 2 * q) * 8);
      };
      if (t == 0) {
        float av[36];
#pragma unroll
        for (int i = 0; i < 36; i++) av[i] = 0.f;
        mma_loop<72, false>(acc, av, R, sb, act0 + w * HALF_BYTES, 8, 0, 0, 1, 0, -1, w == 0, t128, 0);
        mbar_wait(sb + BAR_STAT, 0);
        mbar_expect_tx_pred(sb + BAR_STAT, 144 * 8, tid == 0);
        const float c0 = __shfl_sync(0xffffffffu, av[33], lane | 3), c1 = __shfl_sync(0xffffffffu, av[35], lane | 3);
        float4 st[9];
        load_stats(st);
#pragma unroll
        for (int jj = 0; jj < 9; jj++) {
          pv[2 * jj] = pack_bf16(st[jj].y * fmaf(-st[jj].x, c0, av[4 * jj]), st[jj].w * fmaf(-st[jj].z, c0, av[4 * jj + 1]));
          pv[2 * jj + 1] = pack_bf16(st[jj].y * fmaf(-st[jj].x, c1, av[4 * jj + 2]), st[jj].w * fmaf(-st[jj].z, c1, av[4 * jj + 3]));
        }
      } else {
        mma_loop<72, true>(acc, acc, R, sb, act0 + w * HALF_BYTES, 4, t - 1, 0, 1, 4, -1, w == 0, t128, 0);
      }
      uint32_t p[18];
      if (t < 2) {
        const float c0 = __shfl_sync(0xffffffffu, acc[33], lane | 3), c1 = __shfl_sync(0xffffffffu, acc[35], lane | 3);
        float4 st[9];
        load_stats(st);
#pragma unroll
        for (int i = 0; i < 36; i++) {
          const float m = (i & 1) ? st[i >> 2].z : st[i >> 2].x;
          const float rr = (i & 1) ? st[i >> 2].w : st[i >> 2].y;
          const float u = fmaf(-m, (i & 2) ? c1 : c0, acc[i]);
          const float tl = rr * 1.4426950408889634f * u;
          acc[i] = fmaxf(fmaf(rr, u, 1e-6f), 1e-6f) + ex2(fminf(tl, 0.f));
        }
      }
#pragma unroll
      for (int i = 0; i < 18; i++) p[i] = pack_bf16(acc[(i >> 1) * 4 + (i & 1) * 2], acc[(i >> 1) * 4 + (i & 1) * 2 + 1]);
      if (t == 0) {
        float dkv[2][4] = {}, dz[2][4] = {};
#pragma unroll
        for (int s = 0; s < 5; s++) {
          const int t0 = 16 * s + 2 * q;
          const uint32_t m0 = (t0 < nvalid ? 0x3F80u : 0u) | (t0 + 1 < nvalid ? 0x3F800000u : 0u);
          const uint32_t m1 = (t0 + 8 < nvalid ? 0x3F80u : 0u) | (t0 + 9 < nvalid ? 0x3F800000u : 0u);
#pragma unroll
          for (int h2 = 0; h2 < 2; h2++) {
            const uint32_t b0 = p[4 * s + h2], b1 = s < 4 ? p[(4 * s + 2 + h2) % 18] : 0u;
            mma16816(dkv[h2], pv[4 * s], pv[4 * s + 1], s < 4 ? pv[(4 * s + 2) % 18] : 0u, s < 4 ? pv[(4 * s + 3) % 18] : 0u, b0, b1);
            mma16816(dz[h2], m0, m0, m1, m1, b0, b1);
          }
        }
        asm volatile("bar.sync %0, 160;" ::"r"(12 + w) : "memory");
        unsigned epoch;
        asm volatile("ld.shared.u32 %0, [%1];" : "=r"(epoch) : "r"(sb + OFF_EPOCH) : "memory");
        float* kvg = &g_kv[epoch & 1][(4 * j + w4) * 272];
#pragma unroll
        for (int h2 = 0; h2 < 2; h2++) {
          red_add_v2(kvg + g * 16 + 8 * h2 + 2 * q, dkv[h2][0], dkv[h2][1]);
          red_add_v2(kvg + (g + 8) * 16 + 8 * h2 + 2 * q, dkv[h2][2], dkv[h2][3]);
          if (g == 0) red_add_v2(kvg + 256 + 8 * h2 + 2 * q, dz[h2][0], dz[h2][1]);
        }
        __syncwarp();
        mbar_arrive_pred(sb + BAR_KVDONE, 1, lane == 0);
      } else {
        if (t == 1) {
#pragma unroll
          for (int i = 0; i < 18; i++) p[i] = movmat(p[i]);
          mbar_wait(sb + BAR_KVRDY, 0);
          unsigned epoch;
          asm volatile("ld.shared.u32 %0, [%1];" : "=r"(epoch) : "r"(sb + OFF_EPOCH) : "memory");
          const float* kb = &g_kv[epoch & 1][(4 * j + w4) * 272];
          const float2 f0 = ld_relaxed_v2(kb + g * 16 + 2 * q), f1 = ld_relaxed_v2(kb + (g + 8) * 16 + 2 * q);
          const float2 f2 = ld_relaxed_v2(kb + g * 16 + 8 + 2 * q), f3 = ld_relaxed_v2(kb + (g + 8) * 16 + 8 + 2 * q);
          const float2 z0 = ld_relaxed_v2(kb + 256 + 2 * q), z1 = ld_relaxed_v2(kb + 256 + 8 + 2 * q);
          const uint32_t a0 = pack_bf16(f0.x, f0.y), a1 = pack_bf16(f1.x, f1.y), a2 = pack_bf16(f2.x, f2.y), a3 = pack_bf16(f3.x, f3.y);
          const uint32_t zz0 = pack_bf16(z0.x, z0.y), zz1 = pack_bf16(z1.x, z1.y);
#pragma unroll
          for (int jj = 0; jj < 9; jj++) {
            float num[4] = {}, den[4] = {};
            mma16816(num, a0, a1, a2, a3, p[2 * jj], p[2 * jj + 1]);
            mma16816(den, zz0, zz0, zz1, zz1, p[2 * jj], p[2 * jj + 1]);
            const float r0 = __fdividef(1.f, den[0] + 1e-6f), r1 = __fdividef(1.f, den[1] + 1e-6f);
            p[2 * jj] = pack_bf16(num[0] * r0, num[1] * r1);
            p[2 * jj + 1] = pack_bf16(num[2] * r0, num[3] * r1);
          }
        }
        const uint32_t a = act0 + j * SLOT_BYTES + w * HALF_BYTES + loff;
        stage_frag(a, tail_ok ? a + 8 * 1024 : sb + OFF_DUMMY, p);
        mbar_arrive_pred(sb + BAR_PUB + 8 * (t - 1), 1, lane == 0);
      }
    }
  }
}

__device__ __nv_bfloat16 fb_a[S_TOK * DM], fb_qkv[S_TOK * 3 * DM], fb_o[S_TOK * DM], fb_h[S_TOK * DM], fb_g[S_TOK * FF], fb_u[S_TOK * FF];
__device__ float fb_kv[32 * 272];

__global__ void fb_ln(const __nv_bfloat16* __restrict__ x, __nv_bfloat16* __restrict__ y) {
  const int row = blockIdx.x * 8 + (threadIdx.x >> 5), lane = threadIdx.x & 31;
  float v[16], s = 0.f, ss = 0.f;
  for (int i = 0; i < 16; i++) { v[i] = __bfloat162float(x[(size_t)row * DM + lane + 32 * i]); s += v[i]; }
  for (int o = 16; o > 0; o >>= 1) s += __shfl_xor_sync(0xffffffffu, s, o);
  s *= 1.f / DM;
  for (int i = 0; i < 16; i++) ss += (v[i] - s) * (v[i] - s);
  for (int o = 16; o > 0; o >>= 1) ss += __shfl_xor_sync(0xffffffffu, ss, o);
  const float rs = rsqrtf(ss * (1.f / DM) + 1e-5f);
  for (int i = 0; i < 16; i++) y[(size_t)row * DM + lane + 32 * i] = __float2bfloat16((v[i] - s) * rs);
}
__global__ void fb_gemm(const __nv_bfloat16* __restrict__ A, const __nv_bfloat16* __restrict__ B, __nv_bfloat16* C,
                        const __nv_bfloat16* res, const __nv_bfloat16* mul, int N, int K) {
  __shared__ float sa[16][17], sbm[16][17];
  const int tx = threadIdx.x & 15, ty = threadIdx.x >> 4, row = blockIdx.y * 16 + ty, col = blockIdx.x * 16 + tx;
  float acc = 0.f;
  for (int k0 = 0; k0 < K; k0 += 16) {
    sa[ty][tx] = __bfloat162float(A[(size_t)row * K + k0 + tx]);
    sbm[ty][tx] = __bfloat162float(B[(size_t)(k0 + ty) * N + col]);
    __syncthreads();
    for (int k = 0; k < 16; k++) acc = fmaf(sa[ty][k], sbm[k][tx], acc);
    __syncthreads();
  }
  acc = __bfloat162float(__float2bfloat16(acc));
  if (mul) acc *= __bfloat162float(mul[(size_t)row * N + col]);
  if (res) acc += __bfloat162float(res[(size_t)row * N + col]);
  C[(size_t)row * N + col] = __float2bfloat16(acc);
}
__device__ __forceinline__ float fb_phi(__nv_bfloat16 b) {
  const float t = __bfloat162float(b);
  return __bfloat162float(__float2bfloat16((t > 0.f ? t + 1.f : expf(t)) + 1e-6f));
}
__global__ void fb_kvsum(const __nv_bfloat16* __restrict__ qkv, float* __restrict__ kv) {
  const int h = blockIdx.x, d = threadIdx.x >> 4, e = threadIdx.x & 15;
  float a = 0.f, z = 0.f;
  for (int s = 0; s < S_TOK; s++) {
    const float pk = fb_phi(qkv[(size_t)s * 3 * DM + DM + h * 16 + d]);
    a = fmaf(pk, __bfloat162float(qkv[(size_t)s * 3 * DM + 2 * DM + h * 16 + e]), a);
    z += pk;
  }
  kv[h * 272 + d * 16 + e] = __bfloat162float(__float2bfloat16(a));
  if (e == 0) kv[h * 272 + 256 + d] = __bfloat162float(__float2bfloat16(z));
}
__global__ void fb_attn(const __nv_bfloat16* __restrict__ qkv, const float* __restrict__ kv, __nv_bfloat16* __restrict__ o) {
  const int s = blockIdx.x, c = threadIdx.x, h = c >> 4, e = c & 15;
  float num = 0.f, den = 0.f;
  for (int d = 0; d < 16; d++) {
    const float pq = fb_phi(qkv[(size_t)s * 3 * DM + h * 16 + d]);
    num = fmaf(pq, kv[h * 272 + d * 16 + e], num);
    den = fmaf(pq, kv[h * 272 + 256 + d], den);
  }
  o[(size_t)s * DM + c] = __float2bfloat16(num / (den + 1e-6f));
}

void run_fallback(void* const* d_in, void* d_out) {
  typedef __nv_bfloat16 bf;
  void *a, *qkv, *o, *h, *g, *u, *kv;
  cudaGetSymbolAddress(&a, fb_a); cudaGetSymbolAddress(&qkv, fb_qkv); cudaGetSymbolAddress(&o, fb_o);
  cudaGetSymbolAddress(&h, fb_h); cudaGetSymbolAddress(&g, fb_g); cudaGetSymbolAddress(&u, fb_u); cudaGetSymbolAddress(&kv, fb_kv);
  cudaStream_t st = cudaStreamPerThread;
  const bf* x = (const bf*)d_in[0];
  fb_ln<<<S_TOK / 8, 256, 0, st>>>(x, (bf*)a);
  fb_gemm<<<dim3(3 * DM / 16, S_TOK / 16), 256, 0, st>>>((bf*)a, (const bf*)d_in[1], (bf*)qkv, nullptr, nullptr, 3 * DM, DM);
  fb_kvsum<<<32, 256, 0, st>>>((bf*)qkv, (float*)kv);
  fb_attn<<<S_TOK, DM, 0, st>>>((bf*)qkv, (float*)kv, (bf*)o);
  fb_gemm<<<dim3(DM / 16, S_TOK / 16), 256, 0, st>>>((bf*)o, (const bf*)d_in[2], (bf*)h, x, nullptr, DM, DM);
  fb_ln<<<S_TOK / 8, 256, 0, st>>>((bf*)h, (bf*)a);
  fb_gemm<<<dim3(FF / 16, S_TOK / 16), 256, 0, st>>>((bf*)a, (const bf*)d_in[4], (bf*)g, nullptr, nullptr, FF, DM);
  fb_gemm<<<dim3(FF / 16, S_TOK / 16), 256, 0, st>>>((bf*)a, (const bf*)d_in[5], (bf*)u, nullptr, (bf*)g, FF, DM);
  fb_gemm<<<dim3(DM / 16, S_TOK / 16), 256, 0, st>>>((bf*)u, (const bf*)d_in[6], (bf*)d_out, (bf*)h, nullptr, DM, FF);
}

typedef CUresult (*EncodeFn)(CUtensorMap*, CUtensorMapDataType, cuuint32_t, void*, const cuuint64_t*, const cuuint64_t*,
                             const cuuint32_t*, const cuuint32_t*, CUtensorMapInterleave, CUtensorMapSwizzle,
                             CUtensorMapL2promotion, CUtensorMapFloatOOBfill);

void make_map(EncodeFn enc, CUtensorMap* m, const void* base, int rows, int cols, int box_rows) {
  cuuint64_t dims[2] = {(cuuint64_t)cols, (cuuint64_t)rows};
  cuuint64_t strides[1] = {(cuuint64_t)cols * 2};
  cuuint32_t box[2] = {64, (cuuint32_t)box_rows};
  cuuint32_t es[2] = {1, 1};
  enc(m, CU_TENSOR_MAP_DATA_TYPE_BFLOAT16, 2, const_cast<void*>(base), dims, strides, box, es, CU_TENSOR_MAP_INTERLEAVE_NONE,
      CU_TENSOR_MAP_SWIZZLE_128B, CU_TENSOR_MAP_L2_PROMOTION_L2_128B, CU_TENSOR_MAP_FLOAT_OOB_FILL_NONE);
}

}

extern "C" void kernel_launch(void* const* d_in, const int* in_sizes, int n_in, void* d_out, int out_size) {
  (void)in_sizes; (void)n_in; (void)out_size;
  static EncodeFn enc = nullptr;
  static void* pscr = nullptr;
  static bool fused_ok = false;
  cudaLaunchConfig_t cfg = {};
  cfg.gridDim = dim3(NCL * CL);
  cfg.blockDim = dim3(384);
  cfg.dynamicSmemBytes = SMEM_ALLOC;
  cfg.stream = cudaStreamPerThread;
  cudaLaunchAttribute at[1];
  at[0].id = cudaLaunchAttributeClusterDimension;
  at[0].val.clusterDim.x = CL;
  at[0].val.clusterDim.y = 1;
  at[0].val.clusterDim.z = 1;
  cfg.attrs = at;
  cfg.numAttrs = 1;
  if (!pscr) {
    void* fn = nullptr;
    cudaDriverEntryPointQueryResult qr;
    cudaGetDriverEntryPoint("cuTensorMapEncodeTiled", &fn, cudaEnableDefault, &qr);
    enc = (EncodeFn)fn;
    cudaGetSymbolAddress(&pscr, g_scr);
    cudaFuncSetAttribute(fused_kernel, cudaFuncAttributeMaxDynamicSharedMemorySize, SMEM_ALLOC);
    int nclusters = 0;
    fused_ok = enc && cudaOccupancyMaxActiveClusters(&nclusters, fused_kernel, &cfg) == cudaSuccess && nclusters >= NCL;
    (void)cudaGetLastError();
  }
  if (!fused_ok) {
    run_fallback(d_in, d_out);
    return;
  }
  Params P;
  make_map(enc, &P.x, d_in[0], S_TOK, DM, TH);
  make_map(enc, &P.wqkv, d_in[1], DM, 3 * DM, 64);
  make_map(enc, &P.wo, d_in[2], DM, DM, 64);
  make_map(enc, &P.wg, d_in[4], DM, FF, 64);
  make_map(enc, &P.wu, d_in[5], DM, FF, 64);
  make_map(enc, &P.wd, d_in[6], FF, DM, 64);
  make_map(enc, &P.scr, pscr, NCL * SCR_TILES * TOKC, 64, TH);
  make_map(enc, &P.out, d_out, S_TOK, DM, TH);
  P.p_x = (const __nv_bfloat16*)d_in[0];
  P.p_wqkv = (const __nv_bfloat16*)d_in[1];
  P.p_wo = (const __nv_bfloat16*)d_in[2];
  P.p_wg = (const __nv_bfloat16*)d_in[4];
  P.p_wu = (const __nv_bfloat16*)d_in[5];
  P.p_wd = (const __nv_bfloat16*)d_in[6];
  P.p_scr = (__nv_bfloat16*)pscr;

  cudaLaunchKernelEx(&cfg, fused_kernel, P);
}
```
